```python
import torch

def _softmax(x, axis=-1):
    return torch.softmax(x, dim=axis)
def _gelu(x):
    return torch.nn.functional.gelu(x, approximate="tanh")
def _silu(x):
    return torch.nn.functional.silu(x)
def _sigmoid(x):
    return torch.sigmoid(x)
def _layernorm(x, axis=-1, eps=1e-5):
    m = x.mean(dim=axis, keepdim=True)
    v = x.var(dim=axis, keepdim=True, unbiased=False)
    return (x - m) / torch.sqrt(v + eps)
def _scatter_add(tgt, idx, src, axis=0):
    return tgt.clone().index_add_(axis, idx, src)
def _segment_sum(src, seg, n):
    out = torch.zeros((n,) + src.shape[1:], dtype=src.dtype)
    return out.index_add_(0, seg, src)
def _pad(x, pw):
    flat = tuple(v for pair in reversed(pw) for v in pair)
    return torch.nn.functional.pad(x, flat)

kernel_name = 'sequential_preLN__ssm_conv_h3__glu_gated_geglu__prompt'

def setup_inputs():

    _w = (lambda a: (lambda t: t.to(torch.bfloat16) if t.is_floating_point() else t)(torch.as_tensor(a)))
    def _A_setup():
        B, S, D = 1, 2048, 512
        ks = 4
        return {
            "q": _w((lambda *s: torch.randn(*s, dtype=torch.bfloat16) * 0.05)(B, S, D)),
            "k": _w((lambda *s: torch.randn(*s, dtype=torch.bfloat16) * 0.2)(B, S, D)),
            "v": _w((lambda *s: torch.randn(*s, dtype=torch.bfloat16) * 0.2)(B, S, D)),
            "shift_k": _w((lambda *s: torch.randn(*s, dtype=torch.bfloat16) * 0.2)(D, ks) * 0.5),
            "ssm_k": _w((lambda *s: torch.randn(*s, dtype=torch.bfloat16) * 0.4)(D, S) * (1.0 / S ** 0.5)),
            "ssm_D": _w((lambda *s: torch.randn(*s, dtype=torch.bfloat16) * 0.2)(D)),
        }
    _A_in = _A_setup()

    def _B_setup():
        B, S, Dm, Df = 1, 2048, 512, 1376
        return {
            "x": _w((lambda *s: torch.randn(*s, dtype=torch.bfloat16) * 0.05)(B, S, Dm)),
            "w_gate": _w((lambda *s: torch.randn(*s, dtype=torch.bfloat16) * 0.4)(Dm, Df) * (Dm ** -0.5)),
            "w_up": _w((lambda *s: torch.randn(*s, dtype=torch.bfloat16) * 0.4)(Dm, Df) * (Dm ** -0.5)),
            "w_down": _w((lambda *s: torch.randn(*s, dtype=torch.bfloat16) * 0.4)(Df, Dm) * (Df ** -0.5)),
        }
    _B_in = _B_setup()

    return {
        "A_q": _A_in["q"],
        "A_k": _A_in["k"],
        "A_v": _A_in["v"],
        "A_shift_k": _A_in["shift_k"],
        "A_ssm_k": _A_in["ssm_k"],
        "A_ssm_D": _A_in["ssm_D"],
        "B_x": _B_in["x"],
        "B_w_gate": _B_in["w_gate"],
        "B_w_up": _B_in["w_up"],
        "B_w_down": _B_in["w_down"],
    }

def reference(A_q, A_k, A_v, A_shift_k, A_ssm_k, A_ssm_D, B_x, B_w_gate, B_w_up, B_w_down):
    def _A_ref(q, k, v, shift_k, ssm_k, ssm_D):
        B, S, D = q.shape
        ks = shift_k.shape[-1]
        k_pad = _pad(k, ((0, 0), (ks - 1, 0), (0, 0)))
        k_shift = torch.zeros_like(k)
        for t in range(ks):
            k_shift = k_shift + k_pad[:, t:t + S, :] * shift_k[:, ks - 1 - t][None, None, :]
        kv = k_shift * v
        L = 2 * S
        kv_pad = _pad(kv, ((0, 0), (0, S), (0, 0)))
        kf_pad = _pad(ssm_k, ((0, 0), (0, S)))
        kv_f = (lambda x, axes=(-2,-1): torch.fft.rfft2(x.float(), dim=axes))(kv_pad[:, None, :, :], axes=(1, 2))
        kf_f = (lambda x, axes=(-2,-1): torch.fft.rfft2(x.float(), dim=axes))(kf_pad[:, None, :], axes=(1, 2))
        kf_f = (lambda x, *d: x.permute(*d))(kf_f, 1, 2, 0)
        y_f = kv_f * kf_f[None, :, :, :]
        y = (lambda x, s, axes=(-2,-1): torch.fft.irfft2(x, s=s, dim=axes).to(torch.bfloat16))(y_f, (1, L), axes=(1, 2))[:, 0, :S, :]
        y = y + kv * ssm_D[None, None, :]
        return q * y

    def _B_ref(x, w_gate, w_up, w_down):
        g = torch.einsum("bsd,df->bsf", x, w_gate)
        u = torch.einsum("bsd,df->bsf", x, w_up)
        h = _gelu(g) * u
        return torch.einsum("bsf,fd->bsd", h, w_down)

    x = A_q
    h = x + _A_ref(_layernorm(x, axis=-1), A_k, A_v, A_shift_k, A_ssm_k, A_ssm_D)
    h2 = h + _B_ref(_layernorm(h, axis=-1), B_w_gate, B_w_up, B_w_down)
    return h2
```

```cpp
#include <cuda_runtime.h>
#include <cuda_bf16.h>
#include <cuda.h>
#include <stdint.h>
#include <type_traits>

template <int N> struct WG;
template <> struct WG<16> {
    template <int TB> static __device__ __forceinline__ void rs(float* d, uint32_t a0, uint32_t a1, uint32_t a2, uint32_t a3, uint64_t db) {
        asm volatile("{ .reg .pred p; setp.ne.b32 p, 1, 0;\n"
        "wgmma.mma_async.sync.aligned.m64n16k16.f32.bf16.bf16 {"
        "%0, %1, %2, %3, %4, %5, %6, %7}, "
        "{%8, %9, %10, %11}, %12, p, 1, 1, %13; }"
        :
        "+f"(d[0]), "+f"(d[1]), "+f"(d[2]), "+f"(d[3]), "+f"(d[4]), "+f"(d[5]), "+f"(d[6]), "+f"(d[7])
        : "r"(a0), "r"(a1), "r"(a2), "r"(a3), "l"(db), "n"(TB));
    }
};
template <> struct WG<32> {
    template <int TB> static __device__ __forceinline__ void rs(float* d, uint32_t a0, uint32_t a1, uint32_t a2, uint32_t a3, uint64_t db) {
        asm volatile("{ .reg .pred p; setp.ne.b32 p, 1, 0;\n"
        "wgmma.mma_async.sync.aligned.m64n32k16.f32.bf16.bf16 {"
        "%0, %1, %2, %3, %4, %5, %6, %7, %8, %9, %10, %11, %12, %13, %14, %15}, "
        "{%16, %17, %18, %19}, %20, p, 1, 1, %21; }"
        :
        "+f"(d[0]), "+f"(d[1]), "+f"(d[2]), "+f"(d[3]), "+f"(d[4]), "+f"(d[5]), "+f"(d[6]), "+f"(d[7]),
        "+f"(d[8]), "+f"(d[9]), "+f"(d[10]), "+f"(d[11]), "+f"(d[12]), "+f"(d[13]), "+f"(d[14]), "+f"(d[15])
        : "r"(a0), "r"(a1), "r"(a2), "r"(a3), "l"(db), "n"(TB));
    }
};
template <> struct WG<48> {
    template <int TB> static __device__ __forceinline__ void rs(float* d, uint32_t a0, uint32_t a1, uint32_t a2, uint32_t a3, uint64_t db) {
        asm volatile("{ .reg .pred p; setp.ne.b32 p, 1, 0;\n"
        "wgmma.mma_async.sync.aligned.m64n48k16.f32.bf16.bf16 {"
        "%0, %1, %2, %3, %4, %5, %6, %7, %8, %9, %10, %11, %12, %13, %14, %15, "
        "%16, %17, %18, %19, %20, %21, %22, %23}, "
        "{%24, %25, %26, %27}, %28, p, 1, 1, %29; }"
        :
        "+f"(d[0]), "+f"(d[1]), "+f"(d[2]), "+f"(d[3]), "+f"(d[4]), "+f"(d[5]), "+f"(d[6]), "+f"(d[7]),
        "+f"(d[8]), "+f"(d[9]), "+f"(d[10]), "+f"(d[11]), "+f"(d[12]), "+f"(d[13]), "+f"(d[14]), "+f"(d[15]),
        "+f"(d[16]), "+f"(d[17]), "+f"(d[18]), "+f"(d[19]), "+f"(d[20]), "+f"(d[21]), "+f"(d[22]), "+f"(d[23])
        : "r"(a0), "r"(a1), "r"(a2), "r"(a3), "l"(db), "n"(TB));
    }
    template <int TB> static __device__ __forceinline__ void rs0(float* d, uint32_t a0, uint32_t a1, uint32_t a2, uint32_t a3, uint64_t db) {
        asm volatile("{ .reg .pred p; setp.ne.b32 p, 0, 0;\n"
        "wgmma.mma_async.sync.aligned.m64n48k16.f32.bf16.bf16 {"
        "%0, %1, %2, %3, %4, %5, %6, %7, %8, %9, %10, %11, %12, %13, %14, %15, "
        "%16, %17, %18, %19, %20, %21, %22, %23}, "
        "{%24, %25, %26, %27}, %28, p, 1, 1, %29; }"
        :
        "=f"(d[0]), "=f"(d[1]), "=f"(d[2]), "=f"(d[3]), "=f"(d[4]), "=f"(d[5]), "=f"(d[6]), "=f"(d[7]),
        "=f"(d[8]), "=f"(d[9]), "=f"(d[10]), "=f"(d[11]), "=f"(d[12]), "=f"(d[13]), "=f"(d[14]), "=f"(d[15]),
        "=f"(d[16]), "=f"(d[17]), "=f"(d[18]), "=f"(d[19]), "=f"(d[20]), "=f"(d[21]), "=f"(d[22]), "=f"(d[23])
        : "r"(a0), "r"(a1), "r"(a2), "r"(a3), "l"(db), "n"(TB));
    }
};
template <> struct WG<64> {
    template <int TB> static __device__ __forceinline__ void rs(float* d, uint32_t a0, uint32_t a1, uint32_t a2, uint32_t a3, uint64_t db) {
        asm volatile("{ .reg .pred p; setp.ne.b32 p, 1, 0;\n"
        "wgmma.mma_async.sync.aligned.m64n64k16.f32.bf16.bf16 {"
        "%0, %1, %2, %3, %4, %5, %6, %7, %8, %9, %10, %11, %12, %13, %14, %15, "
        "%16, %17, %18, %19, %20, %21, %22, %23, %24, %25, %26, %27, %28, %29, %30, %31}, "
        "{%32, %33, %34, %35}, %36, p, 1, 1, %37; }"
        :
        "+f"(d[0]), "+f"(d[1]), "+f"(d[2]), "+f"(d[3]), "+f"(d[4]), "+f"(d[5]), "+f"(d[6]), "+f"(d[7]),
        "+f"(d[8]), "+f"(d[9]), "+f"(d[10]), "+f"(d[11]), "+f"(d[12]), "+f"(d[13]), "+f"(d[14]), "+f"(d[15]),
        "+f"(d[16]), "+f"(d[17]), "+f"(d[18]), "+f"(d[19]), "+f"(d[20]), "+f"(d[21]), "+f"(d[22]), "+f"(d[23]),
        "+f"(d[24]), "+f"(d[25]), "+f"(d[26]), "+f"(d[27]), "+f"(d[28]), "+f"(d[29]), "+f"(d[30]), "+f"(d[31])
        : "r"(a0), "r"(a1), "r"(a2), "r"(a3), "l"(db), "n"(TB));
    }
    template <int TB> static __device__ __forceinline__ void rs0(float* d, uint32_t a0, uint32_t a1, uint32_t a2, uint32_t a3, uint64_t db) {
        asm volatile("{ .reg .pred p; setp.ne.b32 p, 0, 0;\n"
        "wgmma.mma_async.sync.aligned.m64n64k16.f32.bf16.bf16 {"
        "%0, %1, %2, %3, %4, %5, %6, %7, %8, %9, %10, %11, %12, %13, %14, %15, "
        "%16, %17, %18, %19, %20, %21, %22, %23, %24, %25, %26, %27, %28, %29, %30, %31}, "
        "{%32, %33, %34, %35}, %36, p, 1, 1, %37; }"
        :
        "=f"(d[0]), "=f"(d[1]), "=f"(d[2]), "=f"(d[3]), "=f"(d[4]), "=f"(d[5]), "=f"(d[6]), "=f"(d[7]),
        "=f"(d[8]), "=f"(d[9]), "=f"(d[10]), "=f"(d[11]), "=f"(d[12]), "=f"(d[13]), "=f"(d[14]), "=f"(d[15]),
        "=f"(d[16]), "=f"(d[17]), "=f"(d[18]), "=f"(d[19]), "=f"(d[20]), "=f"(d[21]), "=f"(d[22]), "=f"(d[23]),
        "=f"(d[24]), "=f"(d[25]), "=f"(d[26]), "=f"(d[27]), "=f"(d[28]), "=f"(d[29]), "=f"(d[30]), "=f"(d[31])
        : "r"(a0), "r"(a1), "r"(a2), "r"(a3), "l"(db), "n"(TB));
    }
    template <int TA, int TB> static __device__ __forceinline__ void ss(float* d, uint64_t da, uint64_t db) {
        asm volatile("{ .reg .pred p; setp.ne.b32 p, 1, 0;\n"
        "wgmma.mma_async.sync.aligned.m64n64k16.f32.bf16.bf16 {"
        "%0, %1, %2, %3, %4, %5, %6, %7, %8, %9, %10, %11, %12, %13, %14, %15, "
        "%16, %17, %18, %19, %20, %21, %22, %23, %24, %25, %26, %27, %28, %29, %30, %31}, "
        "%32, %33, p, 1, 1, %34, %35; }"
        :
        "+f"(d[0]), "+f"(d[1]), "+f"(d[2]), "+f"(d[3]), "+f"(d[4]), "+f"(d[5]), "+f"(d[6]), "+f"(d[7]),
        "+f"(d[8]), "+f"(d[9]), "+f"(d[10]), "+f"(d[11]), "+f"(d[12]), "+f"(d[13]), "+f"(d[14]), "+f"(d[15]),
        "+f"(d[16]), "+f"(d[17]), "+f"(d[18]), "+f"(d[19]), "+f"(d[20]), "+f"(d[21]), "+f"(d[22]), "+f"(d[23]),
        "+f"(d[24]), "+f"(d[25]), "+f"(d[26]), "+f"(d[27]), "+f"(d[28]), "+f"(d[29]), "+f"(d[30]), "+f"(d[31])
        : "l"(da), "l"(db), "n"(TA), "n"(TB));
    }
};
template <> struct WG<80> {
    template <int TB> static __device__ __forceinline__ void rs(float* d, uint32_t a0, uint32_t a1, uint32_t a2, uint32_t a3, uint64_t db) {
        asm volatile("{ .reg .pred p; setp.ne.b32 p, 1, 0;\n"
        "wgmma.mma_async.sync.aligned.m64n80k16.f32.bf16.bf16 {"
        "%0, %1, %2, %3, %4, %5, %6, %7, %8, %9, %10, %11, %12, %13, %14, %15, "
        "%16, %17, %18, %19, %20, %21, %22, %23, %24, %25, %26, %27, %28, %29, %30, %31, "
        "%32, %33, %34, %35, %36, %37, %38, %39}, "
        "{%40, %41, %42, %43}, %44, p, 1, 1, %45; }"
        :
        "+f"(d[0]), "+f"(d[1]), "+f"(d[2]), "+f"(d[3]), "+f"(d[4]), "+f"(d[5]), "+f"(d[6]), "+f"(d[7]),
        "+f"(d[8]), "+f"(d[9]), "+f"(d[10]), "+f"(d[11]), "+f"(d[12]), "+f"(d[13]), "+f"(d[14]), "+f"(d[15]),
        "+f"(d[16]), "+f"(d[17]), "+f"(d[18]), "+f"(d[19]), "+f"(d[20]), "+f"(d[21]), "+f"(d[22]), "+f"(d[23]),
        "+f"(d[24]), "+f"(d[25]), "+f"(d[26]), "+f"(d[27]), "+f"(d[28]), "+f"(d[29]), "+f"(d[30]), "+f"(d[31]),
        "+f"(d[32]), "+f"(d[33]), "+f"(d[34]), "+f"(d[35]), "+f"(d[36]), "+f"(d[37]), "+f"(d[38]), "+f"(d[39])
        : "r"(a0), "r"(a1), "r"(a2), "r"(a3), "l"(db), "n"(TB));
    }
};
template <> struct WG<96> {
    template <int TB> static __device__ __forceinline__ void rs(float* d, uint32_t a0, uint32_t a1, uint32_t a2, uint32_t a3, uint64_t db) {
        asm volatile("{ .reg .pred p; setp.ne.b32 p, 1, 0;\n"
        "wgmma.mma_async.sync.aligned.m64n96k16.f32.bf16.bf16 {"
        "%0, %1, %2, %3, %4, %5, %6, %7, %8, %9, %10, %11, %12, %13, %14, %15, "
        "%16, %17, %18, %19, %20, %21, %22, %23, %24, %25, %26, %27, %28, %29, %30, %31, "
        "%32, %33, %34, %35, %36, %37, %38, %39, %40, %41, %42, %43, %44, %45, %46, %47}, "
        "{%48, %49, %50, %51}, %52, p, 1, 1, %53; }"
        :
        "+f"(d[0]), "+f"(d[1]), "+f"(d[2]), "+f"(d[3]), "+f"(d[4]), "+f"(d[5]), "+f"(d[6]), "+f"(d[7]),
        "+f"(d[8]), "+f"(d[9]), "+f"(d[10]), "+f"(d[11]), "+f"(d[12]), "+f"(d[13]), "+f"(d[14]), "+f"(d[15]),
        "+f"(d[16]), "+f"(d[17]), "+f"(d[18]), "+f"(d[19]), "+f"(d[20]), "+f"(d[21]), "+f"(d[22]), "+f"(d[23]),
        "+f"(d[24]), "+f"(d[25]), "+f"(d[26]), "+f"(d[27]), "+f"(d[28]), "+f"(d[29]), "+f"(d[30]), "+f"(d[31]),
        "+f"(d[32]), "+f"(d[33]), "+f"(d[34]), "+f"(d[35]), "+f"(d[36]), "+f"(d[37]), "+f"(d[38]), "+f"(d[39]),
        "+f"(d[40]), "+f"(d[41]), "+f"(d[42]), "+f"(d[43]), "+f"(d[44]), "+f"(d[45]), "+f"(d[46]), "+f"(d[47])
        : "r"(a0), "r"(a1), "r"(a2), "r"(a3), "l"(db), "n"(TB));
    }
};
template <> struct WG<112> {
    template <int TB> static __device__ __forceinline__ void rs(float* d, uint32_t a0, uint32_t a1, uint32_t a2, uint32_t a3, uint64_t db) {
        asm volatile("{ .reg .pred p; setp.ne.b32 p, 1, 0;\n"
        "wgmma.mma_async.sync.aligned.m64n112k16.f32.bf16.bf16 {"
        "%0, %1, %2, %3, %4, %5, %6, %7, %8, %9, %10, %11, %12, %13, %14, %15, "
        "%16, %17, %18, %19, %20, %21, %22, %23, %24, %25, %26, %27, %28, %29, %30, %31, "
        "%32, %33, %34, %35, %36, %37, %38, %39, %40, %41, %42, %43, %44, %45, %46, %47, "
        "%48, %49, %50, %51, %52, %53, %54, %55}, "
        "{%56, %57, %58, %59}, %60, p, 1, 1, %61; }"
        :
        "+f"(d[0]), "+f"(d[1]), "+f"(d[2]), "+f"(d[3]), "+f"(d[4]), "+f"(d[5]), "+f"(d[6]), "+f"(d[7]),
        "+f"(d[8]), "+f"(d[9]), "+f"(d[10]), "+f"(d[11]), "+f"(d[12]), "+f"(d[13]), "+f"(d[14]), "+f"(d[15]),
        "+f"(d[16]), "+f"(d[17]), "+f"(d[18]), "+f"(d[19]), "+f"(d[20]), "+f"(d[21]), "+f"(d[22]), "+f"(d[23]),
        "+f"(d[24]), "+f"(d[25]), "+f"(d[26]), "+f"(d[27]), "+f"(d[28]), "+f"(d[29]), "+f"(d[30]), "+f"(d[31]),
        "+f"(d[32]), "+f"(d[33]), "+f"(d[34]), "+f"(d[35]), "+f"(d[36]), "+f"(d[37]), "+f"(d[38]), "+f"(d[39]),
        "+f"(d[40]), "+f"(d[41]), "+f"(d[42]), "+f"(d[43]), "+f"(d[44]), "+f"(d[45]), "+f"(d[46]), "+f"(d[47]),
        "+f"(d[48]), "+f"(d[49]), "+f"(d[50]), "+f"(d[51]), "+f"(d[52]), "+f"(d[53]), "+f"(d[54]), "+f"(d[55])
        : "r"(a0), "r"(a1), "r"(a2), "r"(a3), "l"(db), "n"(TB));
    }
};
template <> struct WG<128> {
    template <int TB> static __device__ __forceinline__ void rs(float* d, uint32_t a0, uint32_t a1, uint32_t a2, uint32_t a3, uint64_t db) {
        asm volatile("{ .reg .pred p; setp.ne.b32 p, 1, 0;\n"
        "wgmma.mma_async.sync.aligned.m64n128k16.f32.bf16.bf16 {"
        "%0, %1, %2, %3, %4, %5, %6, %7, %8, %9, %10, %11, %12, %13, %14, %15, "
        "%16, %17, %18, %19, %20, %21, %22, %23, %24, %25, %26, %27, %28, %29, %30, %31, "
        "%32, %33, %34, %35, %36, %37, %38, %39, %40, %41, %42, %43, %44, %45, %46, %47, "
        "%48, %49, %50, %51, %52, %53, %54, %55, %56, %57, %58, %59, %60, %61, %62, %63}, "
        "{%64, %65, %66, %67}, %68, p, 1, 1, %69; }"
        :
        "+f"(d[0]), "+f"(d[1]), "+f"(d[2]), "+f"(d[3]), "+f"(d[4]), "+f"(d[5]), "+f"(d[6]), "+f"(d[7]),
        "+f"(d[8]), "+f"(d[9]), "+f"(d[10]), "+f"(d[11]), "+f"(d[12]), "+f"(d[13]), "+f"(d[14]), "+f"(d[15]),
        "+f"(d[16]), "+f"(d[17]), "+f"(d[18]), "+f"(d[19]), "+f"(d[20]), "+f"(d[21]), "+f"(d[22]), "+f"(d[23]),
        "+f"(d[24]), "+f"(d[25]), "+f"(d[26]), "+f"(d[27]), "+f"(d[28]), "+f"(d[29]), "+f"(d[30]), "+f"(d[31]),
        "+f"(d[32]), "+f"(d[33]), "+f"(d[34]), "+f"(d[35]), "+f"(d[36]), "+f"(d[37]), "+f"(d[38]), "+f"(d[39]),
        "+f"(d[40]), "+f"(d[41]), "+f"(d[42]), "+f"(d[43]), "+f"(d[44]), "+f"(d[45]), "+f"(d[46]), "+f"(d[47]),
        "+f"(d[48]), "+f"(d[49]), "+f"(d[50]), "+f"(d[51]), "+f"(d[52]), "+f"(d[53]), "+f"(d[54]), "+f"(d[55]),
        "+f"(d[56]), "+f"(d[57]), "+f"(d[58]), "+f"(d[59]), "+f"(d[60]), "+f"(d[61]), "+f"(d[62]), "+f"(d[63])
        : "r"(a0), "r"(a1), "r"(a2), "r"(a3), "l"(db), "n"(TB));
    }
    template <int TB> static __device__ __forceinline__ void rs0(float* d, uint32_t a0, uint32_t a1, uint32_t a2, uint32_t a3, uint64_t db) {
        asm volatile("{ .reg .pred p; setp.ne.b32 p, 0, 0;\n"
        "wgmma.mma_async.sync.aligned.m64n128k16.f32.bf16.bf16 {"
        "%0, %1, %2, %3, %4, %5, %6, %7, %8, %9, %10, %11, %12, %13, %14, %15, "
        "%16, %17, %18, %19, %20, %21, %22, %23, %24, %25, %26, %27, %28, %29, %30, %31, "
        "%32, %33, %34, %35, %36, %37, %38, %39, %40, %41, %42, %43, %44, %45, %46, %47, "
        "%48, %49, %50, %51, %52, %53, %54, %55, %56, %57, %58, %59, %60, %61, %62, %63}, "
        "{%64, %65, %66, %67}, %68, p, 1, 1, %69; }"
        :
        "=f"(d[0]), "=f"(d[1]), "=f"(d[2]), "=f"(d[3]), "=f"(d[4]), "=f"(d[5]), "=f"(d[6]), "=f"(d[7]),
        "=f"(d[8]), "=f"(d[9]), "=f"(d[10]), "=f"(d[11]), "=f"(d[12]), "=f"(d[13]), "=f"(d[14]), "=f"(d[15]),
        "=f"(d[16]), "=f"(d[17]), "=f"(d[18]), "=f"(d[19]), "=f"(d[20]), "=f"(d[21]), "=f"(d[22]), "=f"(d[23]),
        "=f"(d[24]), "=f"(d[25]), "=f"(d[26]), "=f"(d[27]), "=f"(d[28]), "=f"(d[29]), "=f"(d[30]), "=f"(d[31]),
        "=f"(d[32]), "=f"(d[33]), "=f"(d[34]), "=f"(d[35]), "=f"(d[36]), "=f"(d[37]), "=f"(d[38]), "=f"(d[39]),
        "=f"(d[40]), "=f"(d[41]), "=f"(d[42]), "=f"(d[43]), "=f"(d[44]), "=f"(d[45]), "=f"(d[46]), "=f"(d[47]),
        "=f"(d[48]), "=f"(d[49]), "=f"(d[50]), "=f"(d[51]), "=f"(d[52]), "=f"(d[53]), "=f"(d[54]), "=f"(d[55]),
        "=f"(d[56]), "=f"(d[57]), "=f"(d[58]), "=f"(d[59]), "=f"(d[60]), "=f"(d[61]), "=f"(d[62]), "=f"(d[63])
        : "r"(a0), "r"(a1), "r"(a2), "r"(a3), "l"(db), "n"(TB));
    }
    template <int TA, int TB> static __device__ __forceinline__ void ss(float* d, uint64_t da, uint64_t db) {
        asm volatile("{ .reg .pred p; setp.ne.b32 p, 1, 0;\n"
        "wgmma.mma_async.sync.aligned.m64n128k16.f32.bf16.bf16 {"
        "%0, %1, %2, %3, %4, %5, %6, %7, %8, %9, %10, %11, %12, %13, %14, %15, "
        "%16, %17, %18, %19, %20, %21, %22, %23, %24, %25, %26, %27, %28, %29, %30, %31, "
        "%32, %33, %34, %35, %36, %37, %38, %39, %40, %41, %42, %43, %44, %45, %46, %47, "
        "%48, %49, %50, %51, %52, %53, %54, %55, %56, %57, %58, %59, %60, %61, %62, %63}, "
        "%64, %65, p, 1, 1, %66, %67; }"
        :
        "+f"(d[0]), "+f"(d[1]), "+f"(d[2]), "+f"(d[3]), "+f"(d[4]), "+f"(d[5]), "+f"(d[6]), "+f"(d[7]),
        "+f"(d[8]), "+f"(d[9]), "+f"(d[10]), "+f"(d[11]), "+f"(d[12]), "+f"(d[13]), "+f"(d[14]), "+f"(d[15]),
        "+f"(d[16]), "+f"(d[17]), "+f"(d[18]), "+f"(d[19]), "+f"(d[20]), "+f"(d[21]), "+f"(d[22]), "+f"(d[23]),
        "+f"(d[24]), "+f"(d[25]), "+f"(d[26]), "+f"(d[27]), "+f"(d[28]), "+f"(d[29]), "+f"(d[30]), "+f"(d[31]),
        "+f"(d[32]), "+f"(d[33]), "+f"(d[34]), "+f"(d[35]), "+f"(d[36]), "+f"(d[37]), "+f"(d[38]), "+f"(d[39]),
        "+f"(d[40]), "+f"(d[41]), "+f"(d[42]), "+f"(d[43]), "+f"(d[44]), "+f"(d[45]), "+f"(d[46]), "+f"(d[47]),
        "+f"(d[48]), "+f"(d[49]), "+f"(d[50]), "+f"(d[51]), "+f"(d[52]), "+f"(d[53]), "+f"(d[54]), "+f"(d[55]),
        "+f"(d[56]), "+f"(d[57]), "+f"(d[58]), "+f"(d[59]), "+f"(d[60]), "+f"(d[61]), "+f"(d[62]), "+f"(d[63])
        : "l"(da), "l"(db), "n"(TA), "n"(TB));
    }
};

namespace {

constexpr int S_ = 2048, D_ = 512, F_ = 1376;
constexpr int NCTA = 128, NTHR = 512;
constexpr float LN_EPS = 1e-5f;

constexpr int NW = 10, NA = 8;
constexpr int PRE = 5;
constexpr int OFF_W = 0;
constexpr int OFF_A = NW * 16384;
constexpr int OFF_MISC = OFF_A + NA * 8192;
constexpr int OFF_STAT = OFF_MISC;
constexpr int OFF_BAR = OFF_MISC + 1024;
constexpr int SMEM_BYTES = OFF_BAR + 1024;
constexpr int KVP = 2176;
constexpr int UT = 9280;
constexpr int HT = 4224;
constexpr int OFF_K = PRE * 16384;
constexpr int OFF_V = OFF_K + 8 * KVP;
constexpr int OFF_X = OFF_V + 8 * KVP;
constexpr int OFF_U = OFF_X + 8 * 2048;
constexpr int OFF_H = OFF_U + 4 * UT;
static_assert(OFF_H + 4 * HT <= OFF_A + 3 * 8192, "conv overlay too large");
constexpr int B_FW = 0, B_EW = 10, B_FA = 20, B_EA = 28, B_KV = 36, B_X = 44, B_U = 52, B_Y = 60, B_OVL = 68, B_FL = 69, NBAR = 77;
constexpr int NB_T0 = 1, NB_T1 = 2, NB_HH = 3  , NB_WG = 5  , NB_E = 7;
constexpr int C_STX = 0, C_H = 16, C_HH = 48, NCNT = 48 + 96;

struct Params {
    CUtensorMap k, v, x, wg, wu, wd, wd48, out;
};

}

__device__ uint4 g_h[32 * 64 * 64];
__device__ uint4 g_hh[32 * 176 * 64];
__device__ float2 g_stx[S_];
__device__ float2 g_sth[S_];
__device__ unsigned g_cnt[NCNT * 32];
__device__ unsigned g_epoch[NCTA];
#define TS(i) do {} while (0)

namespace {

__device__ __forceinline__ void mbar_init(uint32_t b, uint32_t c) { asm volatile("mbarrier.init.shared::cta.b64 [%0], %1;" ::"r"(b), "r"(c) : "memory"); }
__device__ __forceinline__ void mbar_expect(uint32_t b, uint32_t bytes) { asm volatile("mbarrier.arrive.expect_tx.shared::cta.b64 _, [%0], %1;" ::"r"(b), "r"(bytes) : "memory"); }
__device__ __forceinline__ void mbar_arrive(uint32_t b, uint32_t c) { asm volatile("mbarrier.arrive.shared::cta.b64 _, [%0], %1;" ::"r"(b), "r"(c) : "memory"); }
__device__ __forceinline__ void mbar_wait(uint32_t b, uint32_t par) {
    asm volatile(
        "{ .reg .pred p; .reg .u32 n;\n"
        "mov.u32 n, 0;\n"
        "W: mbarrier.try_wait.parity.shared::cta.b64 p, [%0], %1;\n"
        "@p bra D;\n"
        "add.u32 n, n, 1;\n"
        "setp.lt.u32 p, n, 4000000;\n"
        "@p bra W;\n"
        "trap;\n"
        "D: }" ::"r"(b), "r"(par) : "memory");
}
__device__ __forceinline__ void mbar_wait_cl(uint32_t b, uint32_t par) {
    asm volatile(
        "{ .reg .pred p; .reg .u32 n;\n"
        "mov.u32 n, 0;\n"
        "W: mbarrier.try_wait.parity.acquire.cluster.shared::cta.b64 p, [%0], %1;\n"
        "@p bra D;\n"
        "add.u32 n, n, 1;\n"
        "setp.lt.u32 p, n, 4000000;\n"
        "@p bra W;\n"
        "trap;\n"
        "D: }" ::"r"(b), "r"(par) : "memory");
}
__device__ __forceinline__ void poll_ge(const unsigned* p, unsigned target) {
    unsigned v, n = 0;
    do {
        asm volatile("ld.acquire.gpu.global.u32 %0, [%1];" : "=r"(v) : "l"(p) : "memory");
        if (++n > 4000000u) __trap();
    } while ((int)(v - target) < 0);
}
__device__ __forceinline__ void red_add(unsigned* p) { asm volatile("red.relaxed.gpu.global.add.u32 [%0], 1;" ::"l"(p) : "memory"); }
__device__ __forceinline__ void fence_gpu() { asm volatile("fence.acq_rel.gpu;" ::: "memory"); }
__device__ __forceinline__ void nb_sync(int id, int n) { asm volatile("bar.sync %0, %1;" ::"r"(id), "r"(n) : "memory"); }
__device__ __forceinline__ void nb_arrive(int id, int n) { asm volatile("bar.arrive %0, %1;" ::"r"(id), "r"(n) : "memory"); }
__device__ __forceinline__ void cluster_arrive() { asm volatile("barrier.cluster.arrive.release.aligned;" ::: "memory"); }
__device__ __forceinline__ void cluster_wait() { asm volatile("barrier.cluster.wait.acquire.aligned;" ::: "memory"); }
__device__ __forceinline__ uint32_t mapa(uint32_t a, uint32_t r) { uint32_t o; asm("mapa.shared::cluster.u32 %0, %1, %2;" : "=r"(o) : "r"(a), "r"(r)); return o; }
__device__ __forceinline__ void tma2(uint32_t dst, const CUtensorMap* m, int x, int y, uint32_t bar) {
    asm volatile("cp.async.bulk.tensor.2d.shared::cluster.global.mbarrier::complete_tx::bytes [%0], [%1, {%3, %4}], [%2];"
                 ::"r"(dst), "l"(m), "r"(bar), "r"(x), "r"(y) : "memory");
}
__device__ __forceinline__ void tma3(uint32_t dst, const CUtensorMap* m, int x, int y, int z, uint32_t bar) {
    asm volatile("cp.async.bulk.tensor.3d.shared::cluster.global.mbarrier::complete_tx::bytes [%0], [%1, {%3, %4, %5}], [%2];"
                 ::"r"(dst), "l"(m), "r"(bar), "r"(x), "r"(y), "r"(z) : "memory");
}
__device__ __forceinline__ void bulk_ld(uint32_t dst, const void* src, uint32_t bytes, uint32_t bar) {
    asm volatile("cp.async.bulk.shared::cluster.global.mbarrier::complete_tx::bytes [%0], [%1], %2, [%3];"
                 ::"r"(dst), "l"(src), "r"(bytes), "r"(bar) : "memory");
}
__device__ __forceinline__ void l2_prefetch(const void* src, uint32_t bytes) { asm volatile("cp.async.bulk.prefetch.L2.global [%0], %1;" ::"l"(src), "r"(bytes) : "memory"); }
__device__ __forceinline__ uint32_t lds32(uint32_t a) { uint32_t v; asm volatile("ld.shared.u32 %0, [%1];" : "=r"(v) : "r"(a)); return v; }
__device__ __forceinline__ uint2 lds64(uint32_t a) { uint2 v; asm volatile("ld.shared.v2.u32 {%0, %1}, [%2];" : "=r"(v.x), "=r"(v.y) : "r"(a)); return v; }
__device__ __forceinline__ uint4 lds128(uint32_t a) { uint4 v; asm volatile("ld.shared.v4.u32 {%0, %1, %2, %3}, [%4];" : "=r"(v.x), "=r"(v.y), "=r"(v.z), "=r"(v.w) : "r"(a)); return v; }
__device__ __forceinline__ void sts128(uint32_t a, uint4 v) { asm volatile("st.shared.v4.u32 [%0], {%1, %2, %3, %4};" ::"r"(a), "r"(v.x), "r"(v.y), "r"(v.z), "r"(v.w) : "memory"); }
__device__ __forceinline__ void stasync32(uint32_t a, uint32_t v, uint32_t bar) {
    asm volatile("st.async.weak.shared::cluster.mbarrier::complete_tx::bytes.u32 [%0], %1, [%2];" ::"r"(a), "r"(v), "r"(bar) : "memory");
}
__device__ __forceinline__ void stasync128(uint32_t a, uint32_t x, uint32_t y, uint32_t z, uint32_t w, uint32_t bar) {
    asm volatile("st.async.weak.shared::cluster.mbarrier::complete_tx::bytes.v4.u32 [%0], {%1, %2, %3, %4}, [%5];"
                 ::"r"(a), "r"(x), "r"(y), "r"(z), "r"(w), "r"(bar) : "memory");
}
__device__ __forceinline__ uint4 ldg128(const void* p) { uint4 v; asm volatile("ld.global.nc.L1::no_allocate.v4.u32 {%0, %1, %2, %3}, [%4];" : "=r"(v.x), "=r"(v.y), "=r"(v.z), "=r"(v.w) : "l"(p)); return v; }
__device__ __forceinline__ uint32_t pack2(float lo, float hi) { uint32_t r; asm("cvt.rn.bf16x2.f32 %0, %1, %2;" : "=r"(r) : "f"(hi), "f"(lo)); return r; }
__device__ __forceinline__ float bf_lo(uint32_t w) { return __uint_as_float(w << 16); }
__device__ __forceinline__ float bf_hi(uint32_t w) { return __uint_as_float(w & 0xffff0000u); }
__device__ __forceinline__ uint32_t hmul2(uint32_t a, uint32_t b) { uint32_t r; asm("mul.rn.bf16x2 %0, %1, %2;" : "=r"(r) : "r"(a), "r"(b)); return r; }
__device__ __forceinline__ uint32_t hadd2(uint32_t a, uint32_t b) { uint32_t r; asm("add.rn.bf16x2 %0, %1, %2;" : "=r"(r) : "r"(a), "r"(b)); return r; }
__device__ __forceinline__ uint32_t hfma2(uint32_t a, uint32_t b, uint32_t c) { uint32_t r; asm("fma.rn.bf16x2 %0, %1, %2, %3;" : "=r"(r) : "r"(a), "r"(b), "r"(c)); return r; }
__device__ __forceinline__ float tanh_fast(float x) { float r; asm("tanh.approx.f32 %0, %1;" : "=f"(r) : "f"(x)); return r; }
__device__ __forceinline__ uint64_t mkdesc(uint32_t addr, uint32_t lbo, uint32_t sbo, uint32_t mode) {
    return (uint64_t)((addr & 0x3FFFF) >> 4) | ((uint64_t)(lbo >> 4) << 16) | ((uint64_t)(sbo >> 4) << 32) | ((uint64_t)mode << 62);
}
#define WFENCE asm volatile("wgmma.fence.sync.aligned;" ::: "memory")
#define WCOMMIT asm volatile("wgmma.commit_group.sync.aligned;" ::: "memory")
#define WWAIT(n) asm volatile("wgmma.wait_group.sync.aligned " #n ";" ::: "memory")
template <int A, int B> __device__ __forceinline__ void rename(float* d) {
#pragma unroll
    for (int i = A; i < B; i++) { float t; asm volatile("mov.b32 %0, %1;" : "=f"(t) : "f"(d[i]) : "memory"); d[i] = t; }
}
template <int V> using IC = std::integral_constant<int, V>;

template <int NJ>
__device__ __forceinline__ void geglu_store(const float* g, const float* u, const float (&c0)[2], const float (&c1)[2], const float (&kk)[2], uint32_t* dst) {
#pragma unroll
    for (int j = 0; j < NJ; j++) {
#pragma unroll
        for (int r = 0; r < 2; r++) {
            float o[2];
#pragma unroll
            for (int e = 0; e < 2; e++) {
                float a = g[4 * j + 2 * r + e], b = u[4 * j + 2 * r + e];
                float th = tanh_fast(a * fmaf(a * a, c1[r], c0[r]));
                float w = a * b * kk[r];
                o[e] = fmaf(w, th, w);
            }
            asm volatile("st.global.u32 [%0], %1;" ::"l"(dst + j * 256 + r * 32), "r"(pack2(o[0], o[1])) : "memory");
        }
    }
}

}

__global__ void __cluster_dims__(2, 1, 1) __launch_bounds__(NTHR, 1)
h3_geglu_kernel(const __grid_constant__ Params prm, const __nv_bfloat16* __restrict__ xin, const __nv_bfloat16* __restrict__ shift_k,
                const __nv_bfloat16* __restrict__ ssm_k, const __nv_bfloat16* __restrict__ ssm_D, const __nv_bfloat16* __restrict__ w_gate,
                const __nv_bfloat16* __restrict__ w_up, const __nv_bfloat16* __restrict__ w_down) {
    extern __shared__ __align__(1024) unsigned char smem[];
    const uint32_t smb = (uint32_t)__cvta_generic_to_shared(smem);
    const uint32_t bar = smb + OFF_BAR;
    const int tid = threadIdx.x, lane = tid & 31;
    const int warp = __shfl_sync(0xffffffffu, tid >> 5, 0);
    const int rank = blockIdx.x & 1;
    int P;
    {
        int cl = blockIdx.x >> 1, t = cl - 4;
        P = cl < 4 ? cl + 4 : (t < 32 ? (t & 7) * 8 + (t >> 3) : (1 + (t - 32) % 7) * 8 + 4 + (t - 32) / 7);
    }
    const int L = 2 * P + rank;
    const int rr = 4 * (L >> 5) + ((L >> 2) & 3);
    const int jj = 4 * ((L >> 4) & 1) + (L & 3);
    const int R2 = rr + 16 * (jj >> 2), cN = jj & 3;

    if (warp == 8) {
        for (int b = lane; b < NBAR; b += 32) {
            uint32_t c = (b >= B_EW && b < B_FA) ? 8 : (b >= B_EA && b < B_KV) ? 4 : 1;
            mbar_init(bar + 8 * b, c);
            if (b >= B_KV && b < B_OVL) mbar_expect(bar + 8 * b, b < B_X ? 4224 : (b >= B_U && b < B_Y) ? 4096 : 2048);
        }
        asm volatile("fence.mbarrier_init.release.cluster;" ::: "memory");
        asm volatile("fence.proxy.async.shared::cta;" ::: "memory");
        __syncwarp();
        if (lane == 0) {
#pragma unroll 1
            for (int i = 0; i < 2; i++) {
                tma3(smb + OFF_K + i * KVP, &prm.k, 8 * P, 64 * i + 32 * rank - 1, 0, bar + 8 * (B_KV + i));
                tma3(smb + OFF_V + i * KVP, &prm.v, 8 * P, 64 * i + 32 * rank - 1, 0, bar + 8 * (B_KV + i));
            }
        }
        __syncwarp();
    }
    __syncthreads();
    cluster_arrive();

    if (warp < 8) {
        asm volatile("setmaxnreg.inc.sync.aligned.u32 224;");
        const int wg = warp >> 2, w = warp & 3, g = lane >> 2, q = lane & 3, t128 = tid & 127;
        {
            const int ch = 8 * P + 4 * rank + 2 * wg;
            const uint32_t ht = smb + OFF_H + 2 * wg * HT;
            {
                uint4 v[4];
#pragma unroll
                for (int i = 0; i < 4; i++) v[i] = ldg128(ssm_k + (size_t)ch * S_ + (i * 128 + t128) * 8);
                if (t128 < 16) sts128(ht + (t128 >> 2) * 2112 + (t128 & 3) * 16, make_uint4(0, 0, 0, 0));
                else if (t128 < 24) sts128(smb + OFF_U + (2 * wg + ((t128 >> 2) & 1)) * UT + (t128 & 3) * 16, make_uint4(0, 0, 0, 0));
                if (t128 == 0) {
                    uint32_t dd = *(const uint32_t*)(ssm_D + ch);
                    v[0].x = (v[0].x & 0xffff0000u) | (pack2(bf_lo(v[0].x) + bf_lo(dd), 0.f) & 0xffffu);
                    v[2].x = (v[2].x & 0xffff0000u) | (pack2(bf_lo(v[2].x) + bf_hi(dd), 0.f) & 0xffffu);
                }
#pragma unroll
                for (int i = 0; i < 4; i++) sts128(ht + (i >> 1) * HT + (t128 & 1) * 2112 + (4 + (i & 1) * 64 + (t128 >> 1)) * 16, v[i]);
                asm volatile("fence.proxy.async.shared::cta;" ::: "memory");
            }
            cluster_wait();
            nb_sync(NB_WG + wg, 128);
            if (w == 0) TS(wg * 16 + 0);

            const int sig = g >> 1, lam = 2 * w + (g & 1) - 2 * q;
            const uint32_t base1 = smb + OFF_U + 2 * wg * UT + (24 + sig * 72 + lam) * 4;
            const uint32_t base0 = base1 - (lam < 0 ? 32 : 0);
            const uint64_t db0 = mkdesc(ht + 64, 2112, 128, 0), db1 = db0 + (HT >> 4);
            const bool s0 = sig & 1, s1 = sig >> 1, d0 = s0 && q >= 2;
            const uint32_t yoff = OFF_V + (2 * rank + wg) * 512 + (32 * w + (lane ^ w)) * 4;
            const uint32_t cta0 = mapa(smb, 0), cta1 = mapa(smb, 1);
            float acc0[64], acc1[64], hs0[2] = {0.f, 0.f}, hs1[2] = {0.f, 0.f};
            uint32_t a0[16], a1[16];

            auto load = [&](auto Ic, uint32_t(&a)[16], int c) {
                constexpr int I = decltype(Ic)::value;
                const uint32_t o = c * UT + I * 4 * 72 * 4;
                uint32_t p[9];
                p[0] = lds32(base1 + o - 64);
                p[1] = lds32(base0 + o);
#pragma unroll
                for (int m = 1; m < 8; m++) p[m + 1] = lds32(base1 + o + 32 * m);
#pragma unroll
                for (int t = 0; t < 4; t++) { a[4 * t] = p[2 * t + 1]; a[4 * t + 1] = p[2 * t + 2]; a[4 * t + 2] = p[2 * t]; a[4 * t + 3] = p[2 * t + 1]; }
            };
            auto mma = [&](auto Ic, float* acc, uint32_t(&a)[16], uint64_t db) {
                constexpr int I = decltype(Ic)::value;
                WFENCE;
#pragma unroll
                for (int t = 0; t < 4; t++) {
                    if (I == 0 && t == 0) WG<128>::template rs0<0>(acc, a[0], a[1], a[2], a[3], db);
                    else WG<128 - 16 * I>::template rs<0>(acc + 8 * I, a[4 * t], a[4 * t + 1], a[4 * t + 2], a[4 * t + 3], db - t);
                }
                WCOMMIT;
            };
            auto red = [&](auto Ic, const float* acc, float(&hs)[2], float(&r)[2]) {
                constexpr int I = decltype(Ic)::value;
                float s[2][2];
#pragma unroll
                for (int J = 0; J < 2; J++)
#pragma unroll
                    for (int ro = 0; ro < 2; ro++) {
                        const int j = 2 * I + J;
                        float z0 = d0 ? (j > 0 ? acc[4 * (j > 0 ? j - 1 : 0) + 2 * ro] : 0.f) : acc[4 * j + 2 * ro];
                        float z1 = d0 ? (j > 0 ? acc[4 * (j > 0 ? j - 1 : 0) + 2 * ro + 1] : 0.f) : acc[4 * j + 2 * ro + 1];
                        s[J][ro] = (s0 ? z1 : z0) + __shfl_xor_sync(0xffffffffu, s0 ? z0 : z1, 10);
                    }
                r[0] = (s1 ? hs[1] : s[0][0]) + __shfl_xor_sync(0xffffffffu, s1 ? hs[0] : s[0][1], 16);
                r[1] = (s1 ? s[0][1] : s[1][0]) + __shfl_xor_sync(0xffffffffu, s1 ? s[0][0] : s[1][1], 16);
                hs[0] = s[1][0]; hs[1] = s[1][1];
            };
            auto step = [&](auto Ic) {
                constexpr int I = decltype(Ic)::value;
                float r0[2], r1[2];
                if constexpr (I < 7) mbar_wait_cl(bar + 8 * (B_U + I + 1), 0);
                WWAIT(1);
                rename<8 * I, 64>(acc0);
                if constexpr (I < 7) { load(IC<I + 1>{}, a0, 0); mma(IC<I + 1>{}, acc0, a0, db0); }
                red(Ic, acc0, hs0, r0);
                if constexpr (I < 7) WWAIT(1); else WWAIT(0);
                rename<8 * I, 64>(acc1);
                if constexpr (I < 7) { load(IC<I + 1>{}, a1, 1); mma(IC<I + 1>{}, acc1, a1, db1); }
                red(Ic, acc1, hs1, r1);
                stasync32(cta0 + yoff + I * KVP, pack2(r0[0], r1[0]), cta0 + OFF_BAR + 8 * (B_Y + I));
                stasync32(cta1 + yoff + I * KVP, pack2(r0[1], r1[1]), cta1 + OFF_BAR + 8 * (B_Y + I));
                if (w == 0 && (I == 0 || I == 3 || I == 7)) TS(wg * 16 + 2 + (I + 1) / 4);
            };
            mbar_wait_cl(bar + 8 * B_U, 0);
            if (w == 0) TS(wg * 16 + 1);
            load(IC<0>{}, a0, 0); mma(IC<0>{}, acc0, a0, db0);
            load(IC<0>{}, a1, 1); mma(IC<0>{}, acc1, a1, db1);
            step(IC<0>{}); step(IC<1>{}); step(IC<2>{}); step(IC<3>{});
            step(IC<4>{}); step(IC<5>{}); step(IC<6>{}); step(IC<7>{});
        }
        uint32_t ws = 0, wp = 0;
        {
            uint32_t a[128];
            float c0[2], c1[2], kk[2];
            {
                uint32_t nm[2];
                const uint32_t fa = bar + 8 * (wg ? B_FL : B_FA);
                mbar_wait(fa, 0);
                if (w == 0) TS(wg * 16 + 5);
#pragma unroll
                for (int r = 0; r < 2; r++) {
                    uint2 st = lds64(smb + OFF_STAT + wg * 512 + (16 * w + g + 8 * r) * 8);
                    float mean = __uint_as_float(st.x) * (1.f / D_);
                    float var = fmaxf(fmaf(-mean, mean, __uint_as_float(st.y) * (1.f / D_)), 0.f);
                    float rs = rsqrtf(var + LN_EPS);
                    nm[r] = pack2(-mean, -mean);
                    c0[r] = 0.7978845608028654f * rs;
                    c1[r] = (0.7978845608028654f * 0.044715f) * rs * rs * rs;
                    kk[r] = 0.5f * rs * rs;
                }
                const uint32_t la = smb + OFF_A + (lane >> 4) * 1024 + (16 * w + (lane & 15)) * 16;
#pragma unroll
                for (int s = 0; s < 8; s++) {
                    if (s > 0) mbar_wait(fa + 8 * s, 0);
#pragma unroll
                    for (int ks = 0; ks < 4; ks++) {
                        uint32_t* f = a + 16 * s + 4 * ks;
                        asm volatile("ldmatrix.sync.aligned.m8n8.x4.shared.b16 {%0, %1, %2, %3}, [%4];"
                                     : "=r"(f[0]), "=r"(f[1]), "=r"(f[2]), "=r"(f[3]) : "r"(la + ((s + 3) & 7) * 8192 + ks * 2048));
                    }
#pragma unroll
                    for (int i = 0; i < 16; i++) asm volatile("add.rn.bf16x2 %0, %0, %1;" : "+r"(a[16 * s + i]) : "r"(nm[i & 1]));
                    __syncwarp();
                    if (lane == 0) mbar_arrive(bar + 8 * (B_EA + s), 1);
                }
            }
            if (w == 0) TS(wg * 16 + 6);
            uint32_t* hh = (uint32_t*)(g_hh + ((size_t)(rr + 16 * wg) * 176 + 22 * jj) * 64 + 16 * w + g) + q;
            auto chunk = [&](auto Nc, bool wait_turn) {
                constexpr int N = decltype(Nc)::value;
                float gacc[N / 2], uacc[N / 2];
                if (wait_turn) nb_sync(NB_T0 + wg, 256);
                uint32_t prev = 0;
#pragma unroll
                for (int s = 0; s < 8; s++) {
                    mbar_wait(bar + 8 * (B_FW + ws), wp);
                    const uint64_t db = mkdesc(smb + OFF_W + ws * 16384, 8192, 1024, 1);
                    WFENCE;
#pragma unroll
                    for (int ks = 0; ks < 4; ks++) {
                        const uint32_t* f = a + 16 * s + 4 * ks;
                        if (s == 0 && ks == 0) {
                            WG<N>::template rs0<1>(gacc, f[0], f[1], f[2], f[3], db);
                            WG<N>::template rs0<1>(uacc, f[0], f[1], f[2], f[3], db + 512);
                        } else {
                            WG<N>::template rs<1>(gacc, f[0], f[1], f[2], f[3], db + ks * 128);
                            WG<N>::template rs<1>(uacc, f[0], f[1], f[2], f[3], db + 512 + ks * 128);
                        }
                    }
                    WCOMMIT;
                    if (s == 7) nb_arrive(NB_T0 + (wg ^ 1), 256);
                    if (s > 0) { WWAIT(1); if (lane == 0) mbar_arrive(bar + 8 * (B_EW + prev), 1); }
                    prev = ws;
                    if (++ws == NW) { ws = 0; wp ^= 1; }
                }
                WWAIT(0);
                if (lane == 0) mbar_arrive(bar + 8 * (B_EW + prev), 1);
                rename<0, N / 2>(gacc); rename<0, N / 2>(uacc);
                geglu_store<N / 8>(gacc, uacc, c0, c1, kk, hh);
                hh += 8 * 256;
                nb_arrive(NB_HH + wg, 160);
            };
#pragma unroll 1
            for (int c = 0; c < 2; c++) { chunk(IC<64>{}, (c | wg) != 0); if (w == 0) TS(wg * 16 + 7 + c); }
            chunk(IC<48>{}, true);
            if (w == 0) TS(wg * 16 + 9);
        }
        if (wg == 0) {
            float acc[64];
            {
                const uint32_t* hp = (const uint32_t*)(g_h + ((size_t)R2 * 64 + 16 * cN) * 64 + 16 * w + g) + q;
                uint32_t hv[32];
#pragma unroll
                for (int i = 0; i < 32; i++) asm volatile("ld.relaxed.gpu.global.u32 %0, [%1];" : "=r"(hv[i]) : "l"(hp + (i >> 1) * 256 + (i & 1) * 32) : "memory");
#pragma unroll
                for (int i = 0; i < 32; i++) { acc[2 * i] = bf_lo(hv[i]); acc[2 * i + 1] = bf_hi(hv[i]); }
                rename<0, 64>(acc);
            }
            nb_sync(NB_T0, 256);
            if (w == 0) TS(10);
            uint32_t pw = 0;
            auto piece = [&](auto Kc, int p) {
                constexpr int KS = decltype(Kc)::value;
                const uint32_t as = p & 7;
                mbar_wait(bar + 8 * (B_FW + ws), wp);
                mbar_wait(bar + 8 * (B_FA + as), ((p >> 3) & 1) ^ 1);
                const uint64_t da = mkdesc(smb + OFF_A + ((as + 3) & 7) * 8192, 1024, 128, 0);
                const uint64_t db = mkdesc(smb + OFF_W + ws * 16384, 8192, 1024, 1);
                WFENCE;
#pragma unroll
                for (int ks = 0; ks < KS; ks++) WG<128>::template ss<0, 1>(acc, da + ks * 128, db + ks * 128);
                WCOMMIT;
                if (p > 0) {
                    WWAIT(1);
                    if (lane == 0) { mbar_arrive(bar + 8 * (B_EW + pw), 2); mbar_arrive(bar + 8 * (B_EA + ((p - 1) & 7)), 1); }
                }
                pw = ws;
                if (++ws == NW) { ws = 0; wp ^= 1; }
            };
#pragma unroll 1
            for (int p = 0; p < 16; p++) piece(IC<4>{}, p);
            if (w == 0) TS(11);
#pragma unroll 1
            for (int p = 16; p < 24; p++) piece(IC<3>{}, p);
            WWAIT(0);
            rename<0, 64>(acc);
            if (w == 0) TS(12);
            const uint32_t stg = smb + OFF_W + 8 * 16384 + w * 4096;
            const int mat = lane >> 3, row = (mat & 1) * 8 + (lane & 7);
#pragma unroll
            for (int j = 0; j < 16; j += 2) {
                const uint32_t ad = stg + (j >> 3) * 2048 + row * 128 + ((((j & 7) + (mat >> 1)) ^ (lane & 7)) << 4);
                asm volatile("stmatrix.sync.aligned.m8n8.x4.shared.b16 [%0], {%1, %2, %3, %4};" ::"r"(ad),
                             "r"(pack2(acc[4 * j], acc[4 * j + 1])), "r"(pack2(acc[4 * j + 2], acc[4 * j + 3])),
                             "r"(pack2(acc[4 * j + 4], acc[4 * j + 5])), "r"(pack2(acc[4 * j + 6], acc[4 * j + 7])) : "memory");
            }
            asm volatile("fence.proxy.async.shared::cta;" ::: "memory");
            __syncwarp();
            if (lane == 0) {
#pragma unroll
                for (int b = 0; b < 2; b++)
                    asm volatile("cp.async.bulk.tensor.2d.global.shared::cta.bulk_group [%0, {%2, %3}], [%1];"
                                 ::"l"(&prm.out), "r"(stg + b * 2048), "r"(128 * cN + 64 * b), "r"(64 * R2 + 16 * w) : "memory");
                asm volatile("cp.async.bulk.commit_group;" ::: "memory");
                asm volatile("cp.async.bulk.wait_group.read 0;" ::: "memory");
            }
            if (w == 0) TS(13);
        }
    } else if (warp < 12) {
        asm volatile("setmaxnreg.dec.sync.aligned.u32 32;");
        if (warp == 8) {
            if (lane == 0) {
#pragma unroll 1
                for (int i = 2; i < 8; i++) {
                    tma3(smb + OFF_K + i * KVP, &prm.k, 8 * P, 64 * i + 32 * rank - 1, 0, bar + 8 * (B_KV + i));
                    tma3(smb + OFF_V + i * KVP, &prm.v, 8 * P, 64 * i + 32 * rank - 1, 0, bar + 8 * (B_KV + i));
                }
#pragma unroll 1
                for (int i = 0; i < 8; i++) tma2(smb + OFF_X + i * 2048, &prm.x, 8 * P, 256 * i + 128 * rank, bar + 8 * (B_X + i));
                uint32_t ws = 0, wp = 1;
#pragma unroll 1
                for (int n = 0; n < 48; n++) {
                    if (n == PRE) {
                        l2_prefetch((const char*)w_gate + L * 11008, 11008);
                        l2_prefetch((const char*)w_up + L * 11008, 11008);
                        l2_prefetch((const char*)w_down + L * 11008, 11008);
                        mbar_wait(bar + 8 * B_OVL, 0);
                    }
                    if (n >= NW) mbar_wait(bar + 8 * (B_EW + ws), wp);
                    const uint32_t fb = bar + 8 * (B_FW + ws), dst = smb + OFF_W + ws * 16384;
                    if (n < 24) {
                        mbar_expect(fb, 16384);
                        tma2(dst, &prm.wg, 176 * jj + 8 * (n & 24), 64 * (n & 7), fb);
                        tma2(dst + 8192, &prm.wu, 176 * jj + 8 * (n & 24), 64 * (n & 7), fb);
                    } else {
                        const CUtensorMap* m = n < 40 ? &prm.wd : &prm.wd48;
                        mbar_expect(fb, n < 40 ? 16384 : 12288);
                        const int k0 = 176 * (n & 7) + 8 * ((n - 24) & 24);
                        tma2(dst, m, 128 * cN, k0, fb);
                        tma2(dst + 8192, m, 128 * cN + 64, k0, fb);
                    }
                    if (++ws == NW) { ws = 0; wp ^= 1; }
                }
            }
            __syncwarp();
            cluster_wait();
        } else if (warp == 9) {
            cluster_wait();
            if (lane == 0) {
                const unsigned ep = *(volatile unsigned*)&g_epoch[blockIdx.x] + 1;
#pragma unroll 1
                for (int m = 0; m < 40; m++) {
                    const uint32_t as = m & 7, fb = bar + 8 * (((m >> 3) == 1 ? B_FL : B_FA) + as), dst = smb + OFF_A + ((as + 3) & 7) * 8192;
                    if (as == 0) {
                        if (m < 16) poll_ge(&g_cnt[(C_H + rr + 2 * m) * 32], ep * 64);
                        else poll_ge(&g_cnt[(C_HH + R2 * 3 + (m >> 3) - 2) * 32], ep * 8);
                        asm volatile("fence.proxy.async.global;" ::: "memory");
                        TS(32 + (m >> 3));
                    }
                    if (m == PRE) mbar_wait(bar + 8 * B_OVL, 0);
                    if (m >= NA) mbar_wait(bar + 8 * (B_EA + as), ((m >> 3) & 1) ^ 1);
                    if (m < 16) {
                        const int R = rr + 2 * (m & 8);
                        mbar_expect(fb, as == 0 ? 8192 + 512 : 8192);
                        if (as == 0) bulk_ld(smb + OFF_STAT + (m >> 3) * 512, g_sth + R * 64, 512, fb);
                        bulk_ld(dst, g_h + (R * 64 + as * 8) * 64, 8192, fb);
                    } else {
                        const uint32_t bytes = m < 32 ? 8192 : 6144;
                        mbar_expect(fb, bytes);
                        bulk_ld(dst, g_hh + (R2 * 176 + 22 * as + ((m - 16) & 24)) * 64, bytes, fb);
                    }
                }
                *(volatile unsigned*)&g_epoch[blockIdx.x] = ep;
            }
        } else {
            const int hf = lane & 1, l = 16 * (warp - 10) + (lane >> 1);
            uint32_t wt[4][2];
            {
                uint4 s0 = ldg128(shift_k + (8 * P + 4 * hf) * 4), s1 = ldg128(shift_k + (8 * P + 4 * hf) * 4 + 8);
                wt[0][0] = __byte_perm(s0.x, s0.z, 0x5410); wt[1][0] = __byte_perm(s0.x, s0.z, 0x7632);
                wt[2][0] = __byte_perm(s0.y, s0.w, 0x5410); wt[3][0] = __byte_perm(s0.y, s0.w, 0x7632);
                wt[0][1] = __byte_perm(s1.x, s1.z, 0x5410); wt[1][1] = __byte_perm(s1.x, s1.z, 0x7632);
                wt[2][1] = __byte_perm(s1.y, s1.w, 0x5410); wt[3][1] = __byte_perm(s1.y, s1.w, 0x7632);
            }
            const uint32_t dcta = mapa(smb, hf);
            uint32_t src = smb + OFF_K + l * 16 + hf * 8;
            uint32_t dst = dcta + OFF_U + (24 + 144 * rank + 4 * l + 8 * (l >> 4)) * 4;
            cluster_wait();
#pragma unroll 1
            for (int i = 0; i < 8; i++) {
                mbar_wait(bar + 8 * (B_KV + i), 0);
                if (warp == 10 && (i == 0 || i == 7)) TS(40 + (i >> 2));
                uint2 kr[8], u[5];
#pragma unroll
                for (int r = 0; r < 8; r++) kr[r] = lds64(src + (r & 3) * 528 + (r >> 2) * 16);
#pragma unroll
                for (int r = 0; r < 5; r++) {
                    uint2 vv = lds64(src + 8 * KVP + ((r + 3) & 3) * 528 + ((r + 3) >> 2) * 16);
                    u[r].x = hmul2(hfma2(kr[r + 3].x, wt[0][0], hfma2(kr[r + 2].x, wt[1][0], hfma2(kr[r + 1].x, wt[2][0], hmul2(kr[r].x, wt[3][0])))), vv.x);
                    u[r].y = hmul2(hfma2(kr[r + 3].y, wt[0][1], hfma2(kr[r + 2].y, wt[1][1], hfma2(kr[r + 1].y, wt[2][1], hmul2(kr[r].y, wt[3][1])))), vv.y);
                }
                const uint32_t ub = dcta + OFF_BAR + 8 * (B_U + i);
                stasync128(dst, __byte_perm(u[1].x, u[0].x, 0x5410), __byte_perm(u[2].x, u[1].x, 0x5410), __byte_perm(u[3].x, u[2].x, 0x5410), __byte_perm(u[4].x, u[3].x, 0x5410), ub);
                stasync128(dst + UT, __byte_perm(u[1].x, u[0].x, 0x7632), __byte_perm(u[2].x, u[1].x, 0x7632), __byte_perm(u[3].x, u[2].x, 0x7632), __byte_perm(u[4].x, u[3].x, 0x7632), ub);
                stasync128(dst + 2 * UT, __byte_perm(u[1].y, u[0].y, 0x5410), __byte_perm(u[2].y, u[1].y, 0x5410), __byte_perm(u[3].y, u[2].y, 0x5410), __byte_perm(u[4].y, u[3].y, 0x5410), ub);
                stasync128(dst + 3 * UT, __byte_perm(u[1].y, u[0].y, 0x7632), __byte_perm(u[2].y, u[1].y, 0x7632), __byte_perm(u[3].y, u[2].y, 0x7632), __byte_perm(u[4].y, u[3].y, 0x7632), ub);
                src += KVP;
                dst += 288 * 4;
            }
            if (warp == 10) TS(42);
        }
    } else {
        asm volatile("setmaxnreg.dec.sync.aligned.u32 32;");
        const int ew = warp - 12, t = tid & 127;
        const unsigned ep = *(volatile unsigned*)&g_epoch[blockIdx.x] + 1;
        cluster_wait();
        mbar_wait(bar + 8 * B_KV, 0);
#pragma unroll 1
        for (int hb = 0; hb < 2; hb++) {
            const int row0 = 16 * L + 4 * ew + 2 * hb;
            uint4 xv[2][2];
#pragma unroll
            for (int r = 0; r < 2; r++)
#pragma unroll
                for (int c = 0; c < 2; c++) xv[r][c] = ldg128(xin + (size_t)(row0 + r) * D_ + c * 256 + lane * 8);
#pragma unroll
            for (int r = 0; r < 2; r++) {
                const uint32_t wv[8] = {xv[r][0].x, xv[r][0].y, xv[r][0].z, xv[r][0].w, xv[r][1].x, xv[r][1].y, xv[r][1].z, xv[r][1].w};
                float s = 0.f;
#pragma unroll
                for (int i = 0; i < 8; i++) s += bf_lo(wv[i]) + bf_hi(wv[i]);
#pragma unroll
                for (int o = 16; o; o >>= 1) s += __shfl_xor_sync(0xffffffffu, s, o);
                const float mean = s * (1.f / D_);
                float ss = 0.f;
#pragma unroll
                for (int i = 0; i < 8; i++) { float a = bf_lo(wv[i]) - mean, b = bf_hi(wv[i]) - mean; ss = fmaf(a, a, fmaf(b, b, ss)); }
#pragma unroll
                for (int o = 16; o; o >>= 1) ss += __shfl_xor_sync(0xffffffffu, ss, o);
                const float rs = rsqrtf(ss * (1.f / D_) + LN_EPS);
                if (lane == 0) { g_stx[row0 + r] = make_float2(rs, -mean * rs); g_sth[row0 + r] = make_float2(0.f, 0.f); }
            }
        }
        nb_sync(NB_E, 128);
        if (ew == 0) {
            TS(44);
            if (lane == 0) { fence_gpu(); red_add(&g_cnt[(C_STX + (L >> 3)) * 32]); }
        } else if (ew == 1) {
            if (lane < 8) poll_ge(&g_cnt[(C_STX + 2 * lane + rank) * 32], ep * 8);
        }
        __syncwarp();
        nb_sync(NB_E, 128);
        if (ew == 0) TS(45);
        const int ws_ = (t >> 1) & 3, sg = ((t >> 4) & 1) + ((t >> 2) & 2);
        uint32_t ya = smb + OFF_V + (32 * ws_ + ((4 * (2 * sg + (t & 1)) + ((t >> 5) ^ (2 * (sg & 1)))) ^ ws_)) * 4;
        int tok = 128 * rank + t;
#pragma unroll 1
        for (int i = 0; i < 8; i++) {
            float2 st;
            asm volatile("ld.relaxed.gpu.global.v2.f32 {%0, %1}, [%2];" : "=f"(st.x), "=f"(st.y) : "l"(g_stx + tok) : "memory");
            mbar_wait(bar + 8 * (B_X + i), 0);
            const uint4 xq = lds128(smb + OFF_X + i * 2048 + t * 16);
            mbar_wait_cl(bar + 8 * (B_Y + i), 0);
            if (ew == 0 && (i & 3) == 3) TS(46 + (i >> 2) * 2);
            const uint32_t xw[4] = {xq.x, xq.y, xq.z, xq.w};
            uint32_t hw[4];
            float s = 0.f, ss = 0.f;
#pragma unroll
            for (int p = 0; p < 4; p++) {
                const uint32_t yw = lds32(ya + p * 512);
                const float x0 = bf_lo(xw[p]), x1 = bf_hi(xw[p]);
                hw[p] = pack2(fmaf(fmaf(x0, st.x, st.y), bf_lo(yw), x0), fmaf(fmaf(x1, st.x, st.y), bf_hi(yw), x1));
                const float h0 = bf_lo(hw[p]), h1 = bf_hi(hw[p]);
                s += h0 + h1;
                ss = fmaf(h0, h0, fmaf(h1, h1, ss));
            }
            g_h[((tok >> 6) * 64 + P) * 64 + (tok & 63)] = make_uint4(hw[0], hw[1], hw[2], hw[3]);
            asm volatile("red.relaxed.gpu.global.add.v2.f32 [%0], {%1, %2};" ::"l"(g_sth + tok), "f"(s), "f"(ss) : "memory");
            if ((i & 3) == 3) {
                nb_sync(NB_E, 128);
                if (ew == 0) {
                    fence_gpu();
                    if (lane < 8) red_add(&g_cnt[(C_H + 4 * ((i & 4) + (lane >> 1)) + 2 * rank + (lane & 1)) * 32]);
                    TS(47 + (i >> 2) * 2);
                } else if (i == 7 && t == 32) {
                    mbar_arrive(bar + 8 * B_OVL, 1);
                }
                __syncwarp();
            }
            ya += KVP;
            tok += 256;
        }
        if (ew >= 2) {
#pragma unroll 1
            for (int c = 0; c < 3; c++) {
                nb_sync(NB_HH + ew - 2, 160);
                if (lane == 0) { fence_gpu(); red_add(&g_cnt[(C_HH + (rr + 16 * (ew - 2)) * 3 + c) * 32]); }
                __syncwarp();
            }
        }
    }
}

namespace {

typedef CUresult (*EncodeFn)(CUtensorMap*, CUtensorMapDataType, cuuint32_t, void*, const cuuint64_t*, const cuuint64_t*, const cuuint32_t*,
                             const cuuint32_t*, CUtensorMapInterleave, CUtensorMapSwizzle, CUtensorMapL2promotion, CUtensorMapFloatOOBfill);

void encode(EncodeFn fn, CUtensorMap* m, const void* base, int rank, const cuuint64_t* dims, const cuuint64_t* strides, const cuuint32_t* box,
            CUtensorMapSwizzle sw) {
    const cuuint32_t es[3] = {1, 1, 1};
    fn(m, CU_TENSOR_MAP_DATA_TYPE_BFLOAT16, rank, const_cast<void*>(base), dims, strides, box, es, CU_TENSOR_MAP_INTERLEAVE_NONE, sw,
       CU_TENSOR_MAP_L2_PROMOTION_L2_128B, CU_TENSOR_MAP_FLOAT_OOB_FILL_NONE);
}

}

extern "C" void kernel_launch(void* const* d_in, const int* in_sizes, int n_in, void* d_out, int out_size) {
    (void)in_sizes; (void)n_in; (void)out_size;
    const __nv_bfloat16* x = (const __nv_bfloat16*)d_in[0];
    const __nv_bfloat16* wgate = (const __nv_bfloat16*)d_in[7];
    const __nv_bfloat16* wup = (const __nv_bfloat16*)d_in[8];
    const __nv_bfloat16* wdown = (const __nv_bfloat16*)d_in[9];

    void* fnp = nullptr;
    cudaDriverEntryPointQueryResult qr;
    cudaGetDriverEntryPoint("cuTensorMapEncodeTiled", &fnp, cudaEnableDefault, &qr);
    EncodeFn fn = (EncodeFn)fnp;
    Params p;
    {
        const cuuint64_t dims[3] = {D_, S_ / 4, 4}, str[2] = {4 * D_ * 2, D_ * 2};
        const cuuint32_t box[3] = {8, 33, 4};
        encode(fn, &p.k, d_in[1], 3, dims, str, box, CU_TENSOR_MAP_SWIZZLE_NONE);
        encode(fn, &p.v, d_in[2], 3, dims, str, box, CU_TENSOR_MAP_SWIZZLE_NONE);
    }
    {
        const cuuint64_t dims[2] = {D_, S_}, str[1] = {D_ * 2};
        const cuuint32_t bx[2] = {8, 128}, bo[2] = {64, 16};
        encode(fn, &p.x, x, 2, dims, str, bx, CU_TENSOR_MAP_SWIZZLE_NONE);
        encode(fn, &p.out, d_out, 2, dims, str, bo, CU_TENSOR_MAP_SWIZZLE_128B);
    }
    {
        const cuuint64_t dims[2] = {F_, D_}, str[1] = {F_ * 2};
        const cuuint32_t box[2] = {64, 64};
        encode(fn, &p.wg, wgate, 2, dims, str, box, CU_TENSOR_MAP_SWIZZLE_128B);
        encode(fn, &p.wu, wup, 2, dims, str, box, CU_TENSOR_MAP_SWIZZLE_128B);
    }
    {
        const cuuint64_t dims[2] = {D_, F_}, str[1] = {D_ * 2};
        const cuuint32_t b64[2] = {64, 64}, b48[2] = {64, 48};
        encode(fn, &p.wd, wdown, 2, dims, str, b64, CU_TENSOR_MAP_SWIZZLE_128B);
        encode(fn, &p.wd48, wdown, 2, dims, str, b48, CU_TENSOR_MAP_SWIZZLE_128B);
    }
    cudaFuncSetAttribute(h3_geglu_kernel, cudaFuncAttributeMaxDynamicSharedMemorySize, SMEM_BYTES);
    h3_geglu_kernel<<<NCTA, NTHR, SMEM_BYTES>>>(p, x, (const __nv_bfloat16*)d_in[3], (const __nv_bfloat16*)d_in[4],
                                                (const __nv_bfloat16*)d_in[5], wgate, wup, wdown);
}
```

```cpp
#include <cuda_runtime.h>
#include <cuda_bf16.h>
#include <cuda.h>
#include <stdint.h>
#include <type_traits>

template <int N> struct WG;
template <> struct WG<16> {
    template <int TB> static __device__ __forceinline__ void rs(float* d, uint32_t a0, uint32_t a1, uint32_t a2, uint32_t a3, uint64_t db) {
        asm volatile("{ .reg .pred p; setp.ne.b32 p, 1, 0;\n"
        "wgmma.mma_async.sync.aligned.m64n16k16.f32.bf16.bf16 {"
        "%0, %1, %2, %3, %4, %5, %6, %7}, "
        "{%8, %9, %10, %11}, %12, p, 1, 1, %13; }"
        :
        "+f"(d[0]), "+f"(d[1]), "+f"(d[2]), "+f"(d[3]), "+f"(d[4]), "+f"(d[5]), "+f"(d[6]), "+f"(d[7])
        : "r"(a0), "r"(a1), "r"(a2), "r"(a3), "l"(db), "n"(TB));
    }
};
template <> struct WG<32> {
    template <int TB> static __device__ __forceinline__ void rs(float* d, uint32_t a0, uint32_t a1, uint32_t a2, uint32_t a3, uint64_t db) {
        asm volatile("{ .reg .pred p; setp.ne.b32 p, 1, 0;\n"
        "wgmma.mma_async.sync.aligned.m64n32k16.f32.bf16.bf16 {"
        "%0, %1, %2, %3, %4, %5, %6, %7, %8, %9, %10, %11, %12, %13, %14, %15}, "
        "{%16, %17, %18, %19}, %20, p, 1, 1, %21; }"
        :
        "+f"(d[0]), "+f"(d[1]), "+f"(d[2]), "+f"(d[3]), "+f"(d[4]), "+f"(d[5]), "+f"(d[6]), "+f"(d[7]),
        "+f"(d[8]), "+f"(d[9]), "+f"(d[10]), "+f"(d[11]), "+f"(d[12]), "+f"(d[13]), "+f"(d[14]), "+f"(d[15])
        : "r"(a0), "r"(a1), "r"(a2), "r"(a3), "l"(db), "n"(TB));
    }
};
template <> struct WG<48> {
    template <int TB> static __device__ __forceinline__ void rs(float* d, uint32_t a0, uint32_t a1, uint32_t a2, uint32_t a3, uint64_t db) {
        asm volatile("{ .reg .pred p; setp.ne.b32 p, 1, 0;\n"
        "wgmma.mma_async.sync.aligned.m64n48k16.f32.bf16.bf16 {"
        "%0, %1, %2, %3, %4, %5, %6, %7, %8, %9, %10, %11, %12, %13, %14, %15, "
        "%16, %17, %18, %19, %20, %21, %22, %23}, "
        "{%24, %25, %26, %27}, %28, p, 1, 1, %29; }"
        :
        "+f"(d[0]), "+f"(d[1]), "+f"(d[2]), "+f"(d[3]), "+f"(d[4]), "+f"(d[5]), "+f"(d[6]), "+f"(d[7]),
        "+f"(d[8]), "+f"(d[9]), "+f"(d[10]), "+f"(d[11]), "+f"(d[12]), "+f"(d[13]), "+f"(d[14]), "+f"(d[15]),
        "+f"(d[16]), "+f"(d[17]), "+f"(d[18]), "+f"(d[19]), "+f"(d[20]), "+f"(d[21]), "+f"(d[22]), "+f"(d[23])
        : "r"(a0), "r"(a1), "r"(a2), "r"(a3), "l"(db), "n"(TB));
    }
    template <int TB> static __device__ __forceinline__ void rs0(float* d, uint32_t a0, uint32_t a1, uint32_t a2, uint32_t a3, uint64_t db) {
        asm volatile("{ .reg .pred p; setp.ne.b32 p, 0, 0;\n"
        "wgmma.mma_async.sync.aligned.m64n48k16.f32.bf16.bf16 {"
        "%0, %1, %2, %3, %4, %5, %6, %7, %8, %9, %10, %11, %12, %13, %14, %15, "
        "%16, %17, %18, %19, %20, %21, %22, %23}, "
        "{%24, %25, %26, %27}, %28, p, 1, 1, %29; }"
        :
        "=f"(d[0]), "=f"(d[1]), "=f"(d[2]), "=f"(d[3]), "=f"(d[4]), "=f"(d[5]), "=f"(d[6]), "=f"(d[7]),
        "=f"(d[8]), "=f"(d[9]), "=f"(d[10]), "=f"(d[11]), "=f"(d[12]), "=f"(d[13]), "=f"(d[14]), "=f"(d[15]),
        "=f"(d[16]), "=f"(d[17]), "=f"(d[18]), "=f"(d[19]), "=f"(d[20]), "=f"(d[21]), "=f"(d[22]), "=f"(d[23])
        : "r"(a0), "r"(a1), "r"(a2), "r"(a3), "l"(db), "n"(TB));
    }
};
template <> struct WG<64> {
    template <int TB> static __device__ __forceinline__ void rs(float* d, uint32_t a0, uint32_t a1, uint32_t a2, uint32_t a3, uint64_t db) {
        asm volatile("{ .reg .pred p; setp.ne.b32 p, 1, 0;\n"
        "wgmma.mma_async.sync.aligned.m64n64k16.f32.bf16.bf16 {"
        "%0, %1, %2, %3, %4, %5, %6, %7, %8, %9, %10, %11, %12, %13, %14, %15, "
        "%16, %17, %18, %19, %20, %21, %22, %23, %24, %25, %26, %27, %28, %29, %30, %31}, "
        "{%32, %33, %34, %35}, %36, p, 1, 1, %37; }"
        :
        "+f"(d[0]), "+f"(d[1]), "+f"(d[2]), "+f"(d[3]), "+f"(d[4]), "+f"(d[5]), "+f"(d[6]), "+f"(d[7]),
        "+f"(d[8]), "+f"(d[9]), "+f"(d[10]), "+f"(d[11]), "+f"(d[12]), "+f"(d[13]), "+f"(d[14]), "+f"(d[15]),
        "+f"(d[16]), "+f"(d[17]), "+f"(d[18]), "+f"(d[19]), "+f"(d[20]), "+f"(d[21]), "+f"(d[22]), "+f"(d[23]),
        "+f"(d[24]), "+f"(d[25]), "+f"(d[26]), "+f"(d[27]), "+f"(d[28]), "+f"(d[29]), "+f"(d[30]), "+f"(d[31])
        : "r"(a0), "r"(a1), "r"(a2), "r"(a3), "l"(db), "n"(TB));
    }
    template <int TB> static __device__ __forceinline__ void rs0(float* d, uint32_t a0, uint32_t a1, uint32_t a2, uint32_t a3, uint64_t db) {
        asm volatile("{ .reg .pred p; setp.ne.b32 p, 0, 0;\n"
        "wgmma.mma_async.sync.aligned.m64n64k16.f32.bf16.bf16 {"
        "%0, %1, %2, %3, %4, %5, %6, %7, %8, %9, %10, %11, %12, %13, %14, %15, "
        "%16, %17, %18, %19, %20, %21, %22, %23, %24, %25, %26, %27, %28, %29, %30, %31}, "
        "{%32, %33, %34, %35}, %36, p, 1, 1, %37; }"
        :
        "=f"(d[0]), "=f"(d[1]), "=f"(d[2]), "=f"(d[3]), "=f"(d[4]), "=f"(d[5]), "=f"(d[6]), "=f"(d[7]),
        "=f"(d[8]), "=f"(d[9]), "=f"(d[10]), "=f"(d[11]), "=f"(d[12]), "=f"(d[13]), "=f"(d[14]), "=f"(d[15]),
        "=f"(d[16]), "=f"(d[17]), "=f"(d[18]), "=f"(d[19]), "=f"(d[20]), "=f"(d[21]), "=f"(d[22]), "=f"(d[23]),
        "=f"(d[24]), "=f"(d[25]), "=f"(d[26]), "=f"(d[27]), "=f"(d[28]), "=f"(d[29]), "=f"(d[30]), "=f"(d[31])
        : "r"(a0), "r"(a1), "r"(a2), "r"(a3), "l"(db), "n"(TB));
    }
    template <int TA, int TB> static __device__ __forceinline__ void ss(float* d, uint64_t da, uint64_t db) {
        asm volatile("{ .reg .pred p; setp.ne.b32 p, 1, 0;\n"
        "wgmma.mma_async.sync.aligned.m64n64k16.f32.bf16.bf16 {"
        "%0, %1, %2, %3, %4, %5, %6, %7, %8, %9, %10, %11, %12, %13, %14, %15, "
        "%16, %17, %18, %19, %20, %21, %22, %23, %24, %25, %26, %27, %28, %29, %30, %31}, "
        "%32, %33, p, 1, 1, %34, %35; }"
        :
        "+f"(d[0]), "+f"(d[1]), "+f"(d[2]), "+f"(d[3]), "+f"(d[4]), "+f"(d[5]), "+f"(d[6]), "+f"(d[7]),
        "+f"(d[8]), "+f"(d[9]), "+f"(d[10]), "+f"(d[11]), "+f"(d[12]), "+f"(d[13]), "+f"(d[14]), "+f"(d[15]),
        "+f"(d[16]), "+f"(d[17]), "+f"(d[18]), "+f"(d[19]), "+f"(d[20]), "+f"(d[21]), "+f"(d[22]), "+f"(d[23]),
        "+f"(d[24]), "+f"(d[25]), "+f"(d[26]), "+f"(d[27]), "+f"(d[28]), "+f"(d[29]), "+f"(d[30]), "+f"(d[31])
        : "l"(da), "l"(db), "n"(TA), "n"(TB));
    }
};
template <> struct WG<80> {
    template <int TB> static __device__ __forceinline__ void rs(float* d, uint32_t a0, uint32_t a1, uint32_t a2, uint32_t a3, uint64_t db) {
        asm volatile("{ .reg .pred p; setp.ne.b32 p, 1, 0;\n"
        "wgmma.mma_async.sync.aligned.m64n80k16.f32.bf16.bf16 {"
        "%0, %1, %2, %3, %4, %5, %6, %7, %8, %9, %10, %11, %12, %13, %14, %15, "
        "%16, %17, %18, %19, %20, %21, %22, %23, %24, %25, %26, %27, %28, %29, %30, %31, "
        "%32, %33, %34, %35, %36, %37, %38, %39}, "
        "{%40, %41, %42, %43}, %44, p, 1, 1, %45; }"
        :
        "+f"(d[0]), "+f"(d[1]), "+f"(d[2]), "+f"(d[3]), "+f"(d[4]), "+f"(d[5]), "+f"(d[6]), "+f"(d[7]),
        "+f"(d[8]), "+f"(d[9]), "+f"(d[10]), "+f"(d[11]), "+f"(d[12]), "+f"(d[13]), "+f"(d[14]), "+f"(d[15]),
        "+f"(d[16]), "+f"(d[17]), "+f"(d[18]), "+f"(d[19]), "+f"(d[20]), "+f"(d[21]), "+f"(d[22]), "+f"(d[23]),
        "+f"(d[24]), "+f"(d[25]), "+f"(d[26]), "+f"(d[27]), "+f"(d[28]), "+f"(d[29]), "+f"(d[30]), "+f"(d[31]),
        "+f"(d[32]), "+f"(d[33]), "+f"(d[34]), "+f"(d[35]), "+f"(d[36]), "+f"(d[37]), "+f"(d[38]), "+f"(d[39])
        : "r"(a0), "r"(a1), "r"(a2), "r"(a3), "l"(db), "n"(TB));
    }
};
template <> struct WG<96> {
    template <int TB> static __device__ __forceinline__ void rs(float* d, uint32_t a0, uint32_t a1, uint32_t a2, uint32_t a3, uint64_t db) {
        asm volatile("{ .reg .pred p; setp.ne.b32 p, 1, 0;\n"
        "wgmma.mma_async.sync.aligned.m64n96k16.f32.bf16.bf16 {"
        "%0, %1, %2, %3, %4, %5, %6, %7, %8, %9, %10, %11, %12, %13, %14, %15, "
        "%16, %17, %18, %19, %20, %21, %22, %23, %24, %25, %26, %27, %28, %29, %30, %31, "
        "%32, %33, %34, %35, %36, %37, %38, %39, %40, %41, %42, %43, %44, %45, %46, %47}, "
        "{%48, %49, %50, %51}, %52, p, 1, 1, %53; }"
        :
        "+f"(d[0]), "+f"(d[1]), "+f"(d[2]), "+f"(d[3]), "+f"(d[4]), "+f"(d[5]), "+f"(d[6]), "+f"(d[7]),
        "+f"(d[8]), "+f"(d[9]), "+f"(d[10]), "+f"(d[11]), "+f"(d[12]), "+f"(d[13]), "+f"(d[14]), "+f"(d[15]),
        "+f"(d[16]), "+f"(d[17]), "+f"(d[18]), "+f"(d[19]), "+f"(d[20]), "+f"(d[21]), "+f"(d[22]), "+f"(d[23]),
        "+f"(d[24]), "+f"(d[25]), "+f"(d[26]), "+f"(d[27]), "+f"(d[28]), "+f"(d[29]), "+f"(d[30]), "+f"(d[31]),
        "+f"(d[32]), "+f"(d[33]), "+f"(d[34]), "+f"(d[35]), "+f"(d[36]), "+f"(d[37]), "+f"(d[38]), "+f"(d[39]),
        "+f"(d[40]), "+f"(d[41]), "+f"(d[42]), "+f"(d[43]), "+f"(d[44]), "+f"(d[45]), "+f"(d[46]), "+f"(d[47])
        : "r"(a0), "r"(a1), "r"(a2), "r"(a3), "l"(db), "n"(TB));
    }
};
template <> struct WG<112> {
    template <int TB> static __device__ __forceinline__ void rs(float* d, uint32_t a0, uint32_t a1, uint32_t a2, uint32_t a3, uint64_t db) {
        asm volatile("{ .reg .pred p; setp.ne.b32 p, 1, 0;\n"
        "wgmma.mma_async.sync.aligned.m64n112k16.f32.bf16.bf16 {"
        "%0, %1, %2, %3, %4, %5, %6, %7, %8, %9, %10, %11, %12, %13, %14, %15, "
        "%16, %17, %18, %19, %20, %21, %22, %23, %24, %25, %26, %27, %28, %29, %30, %31, "
        "%32, %33, %34, %35, %36, %37, %38, %39, %40, %41, %42, %43, %44, %45, %46, %47, "
        "%48, %49, %50, %51, %52, %53, %54, %55}, "
        "{%56, %57, %58, %59}, %60, p, 1, 1, %61; }"
        :
        "+f"(d[0]), "+f"(d[1]), "+f"(d[2]), "+f"(d[3]), "+f"(d[4]), "+f"(d[5]), "+f"(d[6]), "+f"(d[7]),
        "+f"(d[8]), "+f"(d[9]), "+f"(d[10]), "+f"(d[11]), "+f"(d[12]), "+f"(d[13]), "+f"(d[14]), "+f"(d[15]),
        "+f"(d[16]), "+f"(d[17]), "+f"(d[18]), "+f"(d[19]), "+f"(d[20]), "+f"(d[21]), "+f"(d[22]), "+f"(d[23]),
        "+f"(d[24]), "+f"(d[25]), "+f"(d[26]), "+f"(d[27]), "+f"(d[28]), "+f"(d[29]), "+f"(d[30]), "+f"(d[31]),
        "+f"(d[32]), "+f"(d[33]), "+f"(d[34]), "+f"(d[35]), "+f"(d[36]), "+f"(d[37]), "+f"(d[38]), "+f"(d[39]),
        "+f"(d[40]), "+f"(d[41]), "+f"(d[42]), "+f"(d[43]), "+f"(d[44]), "+f"(d[45]), "+f"(d[46]), "+f"(d[47]),
        "+f"(d[48]), "+f"(d[49]), "+f"(d[50]), "+f"(d[51]), "+f"(d[52]), "+f"(d[53]), "+f"(d[54]), "+f"(d[55])
        : "r"(a0), "r"(a1), "r"(a2), "r"(a3), "l"(db), "n"(TB));
    }
};
template <> struct WG<128> {
    template <int TB> static __device__ __forceinline__ void rs(float* d, uint32_t a0, uint32_t a1, uint32_t a2, uint32_t a3, uint64_t db) {
        asm volatile("{ .reg .pred p; setp.ne.b32 p, 1, 0;\n"
        "wgmma.mma_async.sync.aligned.m64n128k16.f32.bf16.bf16 {"
        "%0, %1, %2, %3, %4, %5, %6, %7, %8, %9, %10, %11, %12, %13, %14, %15, "
        "%16, %17, %18, %19, %20, %21, %22, %23, %24, %25, %26, %27, %28, %29, %30, %31, "
        "%32, %33, %34, %35, %36, %37, %38, %39, %40, %41, %42, %43, %44, %45, %46, %47, "
        "%48, %49, %50, %51, %52, %53, %54, %55, %56, %57, %58, %59, %60, %61, %62, %63}, "
        "{%64, %65, %66, %67}, %68, p, 1, 1, %69; }"
        :
        "+f"(d[0]), "+f"(d[1]), "+f"(d[2]), "+f"(d[3]), "+f"(d[4]), "+f"(d[5]), "+f"(d[6]), "+f"(d[7]),
        "+f"(d[8]), "+f"(d[9]), "+f"(d[10]), "+f"(d[11]), "+f"(d[12]), "+f"(d[13]), "+f"(d[14]), "+f"(d[15]),
        "+f"(d[16]), "+f"(d[17]), "+f"(d[18]), "+f"(d[19]), "+f"(d[20]), "+f"(d[21]), "+f"(d[22]), "+f"(d[23]),
        "+f"(d[24]), "+f"(d[25]), "+f"(d[26]), "+f"(d[27]), "+f"(d[28]), "+f"(d[29]), "+f"(d[30]), "+f"(d[31]),
        "+f"(d[32]), "+f"(d[33]), "+f"(d[34]), "+f"(d[35]), "+f"(d[36]), "+f"(d[37]), "+f"(d[38]), "+f"(d[39]),
        "+f"(d[40]), "+f"(d[41]), "+f"(d[42]), "+f"(d[43]), "+f"(d[44]), "+f"(d[45]), "+f"(d[46]), "+f"(d[47]),
        "+f"(d[48]), "+f"(d[49]), "+f"(d[50]), "+f"(d[51]), "+f"(d[52]), "+f"(d[53]), "+f"(d[54]), "+f"(d[55]),
        "+f"(d[56]), "+f"(d[57]), "+f"(d[58]), "+f"(d[59]), "+f"(d[60]), "+f"(d[61]), "+f"(d[62]), "+f"(d[63])
        : "r"(a0), "r"(a1), "r"(a2), "r"(a3), "l"(db), "n"(TB));
    }
    template <int TB> static __device__ __forceinline__ void rs0(float* d, uint32_t a0, uint32_t a1, uint32_t a2, uint32_t a3, uint64_t db) {
        asm volatile("{ .reg .pred p; setp.ne.b32 p, 0, 0;\n"
        "wgmma.mma_async.sync.aligned.m64n128k16.f32.bf16.bf16 {"
        "%0, %1, %2, %3, %4, %5, %6, %7, %8, %9, %10, %11, %12, %13, %14, %15, "
        "%16, %17, %18, %19, %20, %21, %22, %23, %24, %25, %26, %27, %28, %29, %30, %31, "
        "%32, %33, %34, %35, %36, %37, %38, %39, %40, %41, %42, %43, %44, %45, %46, %47, "
        "%48, %49, %50, %51, %52, %53, %54, %55, %56, %57, %58, %59, %60, %61, %62, %63}, "
        "{%64, %65, %66, %67}, %68, p, 1, 1, %69; }"
        :
        "=f"(d[0]), "=f"(d[1]), "=f"(d[2]), "=f"(d[3]), "=f"(d[4]), "=f"(d[5]), "=f"(d[6]), "=f"(d[7]),
        "=f"(d[8]), "=f"(d[9]), "=f"(d[10]), "=f"(d[11]), "=f"(d[12]), "=f"(d[13]), "=f"(d[14]), "=f"(d[15]),
        "=f"(d[16]), "=f"(d[17]), "=f"(d[18]), "=f"(d[19]), "=f"(d[20]), "=f"(d[21]), "=f"(d[22]), "=f"(d[23]),
        "=f"(d[24]), "=f"(d[25]), "=f"(d[26]), "=f"(d[27]), "=f"(d[28]), "=f"(d[29]), "=f"(d[30]), "=f"(d[31]),
        "=f"(d[32]), "=f"(d[33]), "=f"(d[34]), "=f"(d[35]), "=f"(d[36]), "=f"(d[37]), "=f"(d[38]), "=f"(d[39]),
        "=f"(d[40]), "=f"(d[41]), "=f"(d[42]), "=f"(d[43]), "=f"(d[44]), "=f"(d[45]), "=f"(d[46]), "=f"(d[47]),
        "=f"(d[48]), "=f"(d[49]), "=f"(d[50]), "=f"(d[51]), "=f"(d[52]), "=f"(d[53]), "=f"(d[54]), "=f"(d[55]),
        "=f"(d[56]), "=f"(d[57]), "=f"(d[58]), "=f"(d[59]), "=f"(d[60]), "=f"(d[61]), "=f"(d[62]), "=f"(d[63])
        : "r"(a0), "r"(a1), "r"(a2), "r"(a3), "l"(db), "n"(TB));
    }
    template <int TA, int TB> static __device__ __forceinline__ void ss(float* d, uint64_t da, uint64_t db) {
        asm volatile("{ .reg .pred p; setp.ne.b32 p, 1, 0;\n"
        "wgmma.mma_async.sync.aligned.m64n128k16.f32.bf16.bf16 {"
        "%0, %1, %2, %3, %4, %5, %6, %7, %8, %9, %10, %11, %12, %13, %14, %15, "
        "%16, %17, %18, %19, %20, %21, %22, %23, %24, %25, %26, %27, %28, %29, %30, %31, "
        "%32, %33, %34, %35, %36, %37, %38, %39, %40, %41, %42, %43, %44, %45, %46, %47, "
        "%48, %49, %50, %51, %52, %53, %54, %55, %56, %57, %58, %59, %60, %61, %62, %63}, "
        "%64, %65, p, 1, 1, %66, %67; }"
        :
        "+f"(d[0]), "+f"(d[1]), "+f"(d[2]), "+f"(d[3]), "+f"(d[4]), "+f"(d[5]), "+f"(d[6]), "+f"(d[7]),
        "+f"(d[8]), "+f"(d[9]), "+f"(d[10]), "+f"(d[11]), "+f"(d[12]), "+f"(d[13]), "+f"(d[14]), "+f"(d[15]),
        "+f"(d[16]), "+f"(d[17]), "+f"(d[18]), "+f"(d[19]), "+f"(d[20]), "+f"(d[21]), "+f"(d[22]), "+f"(d[23]),
        "+f"(d[24]), "+f"(d[25]), "+f"(d[26]), "+f"(d[27]), "+f"(d[28]), "+f"(d[29]), "+f"(d[30]), "+f"(d[31]),
        "+f"(d[32]), "+f"(d[33]), "+f"(d[34]), "+f"(d[35]), "+f"(d[36]), "+f"(d[37]), "+f"(d[38]), "+f"(d[39]),
        "+f"(d[40]), "+f"(d[41]), "+f"(d[42]), "+f"(d[43]), "+f"(d[44]), "+f"(d[45]), "+f"(d[46]), "+f"(d[47]),
        "+f"(d[48]), "+f"(d[49]), "+f"(d[50]), "+f"(d[51]), "+f"(d[52]), "+f"(d[53]), "+f"(d[54]), "+f"(d[55]),
        "+f"(d[56]), "+f"(d[57]), "+f"(d[58]), "+f"(d[59]), "+f"(d[60]), "+f"(d[61]), "+f"(d[62]), "+f"(d[63])
        : "l"(da), "l"(db), "n"(TA), "n"(TB));
    }
};

namespace {

constexpr int S_ = 2048, D_ = 512, F_ = 1376;
constexpr int NCTA = 128, NGRID = 132, NTHR = 512;
constexpr float LN_EPS = 1e-5f;
constexpr int KV_AHEAD = 4, XL_AT = 2, X_AT = 1, X2_AT = 5, G_AT = 2, GL_AT = 6, W_AT = 4;
constexpr int W_AFTER = 3, WL_AFTER = 3, DA = 3, DW2 = 3, PF_DELAY = 1000;
constexpr int PACE = 2, PACE2 = 2, PACE3 = 0, RES_EARLY = 16, G2_AFTER = 4;

constexpr int NW = 10, PRE = 6;
constexpr int OFF_W = 0;
constexpr int OFF_A = NW * 16384;
constexpr int KVP = 2176;
constexpr int UT = 9280;
constexpr int HT = 4224;
constexpr int OFF_K = PRE * 16384;
constexpr int OFF_V = OFF_K + 8 * KVP;
constexpr int OFF_U = OFF_V + 8 * KVP;
constexpr int OFF_H = OFF_U + 4 * UT;
constexpr int OFF_X = OFF_H + 4 * HT;
constexpr int OFF_XR = OFF_X + 8 * 2048;
constexpr int OFF_SX = OFF_XR + 16384;
constexpr int OFF_STAT = OFF_A + 8 * 8192;
static_assert(OFF_SX + 8192 <= OFF_STAT && OFF_X % 128 == 0, "conv overlay too large");
constexpr int OFF_BAR = OFF_STAT + 1024;
constexpr int SMEM_BYTES = OFF_BAR + 1408;
static_assert(SMEM_BYTES <= 232448, "smem");
constexpr int B_KV = 0, B_X = 8  , B_XR = 10  , B_SX = 12  , B_U = 16, B_Y = 24, B_FA = 32, B_EA = 40, B_FL = 48;
constexpr int B_OVL = 56, B_OVW = 61, B_FG = 74  , B_EW = 80, B_G2 = 96  , B_FW = 128  ;
constexpr int NB_T0 = 1  , NB_WG = 3  , NB_E = 5, NB_R = 6, NB_HH = 7  , NB_U = 10;
constexpr int C_H = 0, C_HH = 32, C_Z = 80, NCNT = 96;

struct Params {
    CUtensorMap k, v, x, wg, wu, wd, wd48;
};

}

struct Scratch {
    uint4 h[32 * 64 * 64];
    uint4 hh[32 * 176 * 64];
    float2 sth[8 * S_];
    float2 stx[S_];
    unsigned cnt[NCNT * 32];
    unsigned epoch[NGRID];
};
__device__ __align__(1024) Scratch g_scr;

namespace {

__device__ __forceinline__ void mbar_init(uint32_t b, uint32_t c) { asm volatile("mbarrier.init.shared::cta.b64 [%0], %1;" ::"r"(b), "r"(c) : "memory"); }
__device__ __forceinline__ void mbar_expect(uint32_t b, uint32_t bytes) { asm volatile("mbarrier.arrive.expect_tx.shared::cta.b64 _, [%0], %1;" ::"r"(b), "r"(bytes) : "memory"); }
__device__ __forceinline__ void mbar_arrive(uint32_t b) { asm volatile("mbarrier.arrive.shared::cta.b64 _, [%0];" ::"r"(b) : "memory"); }
__device__ __forceinline__ void mbar_wait(uint32_t b, uint32_t par) {
    asm volatile(
        "{ .reg .pred p; .reg .u32 n;\n"
        "mov.u32 n, 0;\n"
        "W: mbarrier.try_wait.parity.shared::cta.b64 p, [%0], %1;\n"
        "@p bra D;\n"
        "add.u32 n, n, 1;\n"
        "setp.lt.u32 p, n, 2000000;\n"
        "@p bra W;\n"
        "trap;\n"
        "D: }" ::"r"(b), "r"(par) : "memory");
}
__device__ __forceinline__ void poll_ge(const unsigned* p, unsigned target) {
    unsigned v, n = 0;
    do {
        asm volatile("ld.relaxed.gpu.global.u32 %0, [%1];" : "=r"(v) : "l"(p) : "memory");
        if (++n > 4000000u) __trap();
    } while ((int)(v - target) < 0);
    asm volatile("fence.acquire.gpu;" ::: "memory");
}
__device__ __forceinline__ uint32_t mbar_test(uint32_t b, uint32_t par) {
    uint32_t ok;
    asm volatile("{ .reg .pred p; mbarrier.test_wait.parity.shared::cta.b64 p, [%1], %2; selp.u32 %0, 1, 0, p; }" : "=r"(ok) : "r"(b), "r"(par) : "memory");
    return ok;
}
__device__ __forceinline__ void red_add(unsigned* p) { asm volatile("red.relaxed.gpu.global.add.u32 [%0], 1;" ::"l"(p) : "memory"); }
__device__ __forceinline__ void fence_gpu() { asm volatile("fence.release.gpu;" ::: "memory"); }
__device__ __forceinline__ void sync_publish(int id, int n, unsigned* p, bool c) {
    asm volatile("{ .reg .pred p; setp.ne.u32 p, %3, 0;\n bar.sync %0, %1;\n fence.release.gpu;\n @p red.relaxed.gpu.global.add.u32 [%2], 1; }"
                 ::"r"(id), "r"(n), "l"(p), "r"((uint32_t)c) : "memory");
}
__device__ __forceinline__ void nb_sync(int id, int n) { asm volatile("bar.sync %0, %1;" ::"r"(id), "r"(n) : "memory"); }
__device__ __forceinline__ void nb_arrive(int id, int n) { asm volatile("bar.arrive %0, %1;" ::"r"(id), "r"(n) : "memory"); }
__device__ __forceinline__ void cluster_arrive() { asm volatile("barrier.cluster.arrive.relaxed.aligned;" ::: "memory"); }
__device__ __forceinline__ void cluster_wait() { asm volatile("barrier.cluster.wait.acquire.aligned;" ::: "memory"); }
__device__ __forceinline__ bool elect_one() {
    uint32_t p;
    asm volatile("{ .reg .pred e; elect.sync _|e, 0xffffffff; selp.u32 %0, 1, 0, e; }" : "=r"(p));
    return p;
}
__device__ __forceinline__ uint32_t mapa(uint32_t a, uint32_t r) { uint32_t o; asm("mapa.shared::cluster.u32 %0, %1, %2;" : "=r"(o) : "r"(a), "r"(r)); return o; }
__device__ __forceinline__ void tma2_mc(uint32_t dst, const CUtensorMap* m, int x, int y, uint32_t bar) {
    asm volatile("cp.async.bulk.tensor.2d.shared::cluster.global.mbarrier::complete_tx::bytes.multicast::cluster [%0], [%1, {%3, %4}], [%2], %5;"
                 ::"r"(dst), "l"(m), "r"(bar), "r"(x), "r"(y), "h"((uint16_t)3) : "memory");
}
__device__ __forceinline__ void mbar_arrive_cl(uint32_t b) { asm volatile("mbarrier.arrive.shared::cluster.b64 _, [%0];" ::"r"(b) : "memory"); }
__device__ __forceinline__ void mbar_arrive_if(uint32_t b, bool c) { asm volatile("{ .reg .pred p; setp.ne.u32 p, %1, 0; @p mbarrier.arrive.shared::cta.b64 _, [%0]; }" ::"r"(b), "r"((uint32_t)c) : "memory"); }
__device__ __forceinline__ void mbar_arrive_cl_if(uint32_t b, bool c) { asm volatile("{ .reg .pred p; setp.ne.u32 p, %1, 0; @p mbarrier.arrive.shared::cluster.b64 _, [%0]; }" ::"r"(b), "r"((uint32_t)c) : "memory"); }
__device__ __forceinline__ void tma3(uint32_t dst, const CUtensorMap* m, int x, int y, int z, uint32_t bar) {
    asm volatile("cp.async.bulk.tensor.3d.shared::cluster.global.mbarrier::complete_tx::bytes [%0], [%1, {%3, %4, %5}], [%2];"
                 ::"r"(dst), "l"(m), "r"(bar), "r"(x), "r"(y), "r"(z) : "memory");
}
__device__ __forceinline__ void bulk_ld(uint32_t dst, const void* src, uint32_t bytes, uint32_t bar) {
    asm volatile("cp.async.bulk.shared::cluster.global.mbarrier::complete_tx::bytes [%0], [%1], %2, [%3];"
                 ::"r"(dst), "l"(src), "r"(bytes), "r"(bar) : "memory");
}
__device__ __forceinline__ void l2_prefetch(const void* src, uint32_t bytes) { asm volatile("cp.async.bulk.prefetch.L2.global [%0], %1;" ::"l"(src), "r"(bytes) : "memory"); }
__device__ __forceinline__ uint32_t lds32(uint32_t a) { uint32_t v; asm volatile("ld.shared.u32 %0, [%1];" : "=r"(v) : "r"(a)); return v; }
__device__ __forceinline__ uint2 lds64(uint32_t a) { uint2 v; asm volatile("ld.shared.v2.u32 {%0, %1}, [%2];" : "=r"(v.x), "=r"(v.y) : "r"(a)); return v; }
__device__ __forceinline__ uint4 lds128(uint32_t a) { uint4 v; asm volatile("ld.shared.v4.u32 {%0, %1, %2, %3}, [%4];" : "=r"(v.x), "=r"(v.y), "=r"(v.z), "=r"(v.w) : "r"(a)); return v; }
__device__ __forceinline__ void sts128(uint32_t a, uint4 v) { asm volatile("st.shared.v4.u32 [%0], {%1, %2, %3, %4};" ::"r"(a), "r"(v.x), "r"(v.y), "r"(v.z), "r"(v.w) : "memory"); }
__device__ __forceinline__ void stasync32(uint32_t a, uint32_t v, uint32_t bar) {
    asm volatile("st.async.weak.shared::cluster.mbarrier::complete_tx::bytes.u32 [%0], %1, [%2];" ::"r"(a), "r"(v), "r"(bar) : "memory");
}
__device__ __forceinline__ void stasync128(uint32_t a, uint32_t x, uint32_t y, uint32_t z, uint32_t w, uint32_t bar) {
    asm volatile("st.async.weak.shared::cluster.mbarrier::complete_tx::bytes.v4.u32 [%0], {%1, %2, %3, %4}, [%5];"
                 ::"r"(a), "r"(x), "r"(y), "r"(z), "r"(w), "r"(bar) : "memory");
}
__device__ __forceinline__ uint4 ldg128(const void* p) { uint4 v; asm volatile("ld.global.nc.L1::no_allocate.v4.u32 {%0, %1, %2, %3}, [%4];" : "=r"(v.x), "=r"(v.y), "=r"(v.z), "=r"(v.w) : "l"(p)); return v; }
__device__ __forceinline__ uint32_t pack2(float lo, float hi) { uint32_t r; asm("cvt.rn.bf16x2.f32 %0, %1, %2;" : "=r"(r) : "f"(hi), "f"(lo)); return r; }
__device__ __forceinline__ float bf_lo(uint32_t w) { return __uint_as_float(w << 16); }
__device__ __forceinline__ float bf_hi(uint32_t w) { return __uint_as_float(w & 0xffff0000u); }
__device__ __forceinline__ uint32_t hmul2(uint32_t a, uint32_t b) { uint32_t r; asm("mul.rn.bf16x2 %0, %1, %2;" : "=r"(r) : "r"(a), "r"(b)); return r; }
__device__ __forceinline__ uint32_t hadd2(uint32_t a, uint32_t b) { uint32_t r; asm("add.rn.bf16x2 %0, %1, %2;" : "=r"(r) : "r"(a), "r"(b)); return r; }
__device__ __forceinline__ uint32_t hfma2(uint32_t a, uint32_t b, uint32_t c) { uint32_t r; asm("fma.rn.bf16x2 %0, %1, %2, %3;" : "=r"(r) : "r"(a), "r"(b), "r"(c)); return r; }
__device__ __forceinline__ float tanh_fast(float x) { float r; asm("tanh.approx.f32 %0, %1;" : "=f"(r) : "f"(x)); return r; }
constexpr uint32_t SM0 = 1024;
constexpr __host__ __device__ __forceinline__ uint64_t mkdesc(uint32_t addr, uint32_t lbo, uint32_t sbo, uint32_t mode) {
    return (uint64_t)((addr & 0x3FFFF) >> 4) | ((uint64_t)(lbo >> 4) << 16) | ((uint64_t)(sbo >> 4) << 32) | ((uint64_t)mode << 62);
}
#define WFENCE asm volatile("wgmma.fence.sync.aligned;" ::: "memory")
#define WCOMMIT asm volatile("wgmma.commit_group.sync.aligned;" ::: "memory")
#define WWAIT(n) asm volatile("wgmma.wait_group.sync.aligned " #n ";" ::: "memory")
template <int A, int B> __device__ __forceinline__ void rename(float* d) {
#pragma unroll
    for (int i = A; i < B; i++) { float t; asm volatile("mov.b32 %0, %1;" : "=f"(t) : "f"(d[i]) : "memory"); d[i] = t; }
}
__device__ __forceinline__ int chunk_grp(int j, int c) { return (j & 1) ? (c == 2 ? 0 : 6 + 8 * c) : 8 * c; }
template <int V> using IC = std::integral_constant<int, V>;

template <int J0, int J1, int PACE>
__device__ __forceinline__ void geglu_store(const float* g, const float* u, const float (&c0)[2], const float (&c1)[2], const float (&kk)[2],
                                            uint32_t* dst, uint32_t zero, uint32_t (&prev)[2]) {
#pragma unroll
    for (int j = J0; j < J1; j++) {
#pragma unroll
        for (int r = 0; r < 2; r++) {
            float o[2];
            uint32_t& pv = prev[PACE == 2 ? r : 0];
            const float cc = PACE ? __uint_as_float(__float_as_uint(c1[r]) | (pv & zero)) : c1[r];
#pragma unroll
            for (int e = 0; e < 2; e++) {
                const float a = g[4 * j + 2 * r + e], b = u[4 * j + 2 * r + e];
                const float th = tanh_fast(a * fmaf(a * a, cc, c0[r]));
                o[e] = (a * b) * fmaf(th, kk[r], kk[r]);
            }
            pv = pack2(o[0], o[1]);
            asm volatile("st.global.u32 [%0], %1;" ::"l"(dst + j * 256 + r * 32), "r"(pv) : "memory");
        }
    }
}

}

__global__ void __cluster_dims__(2, 1, 1) __launch_bounds__(NTHR, 1)
h3_geglu_kernel(const __nv_bfloat16* __restrict__ ssm_k, Scratch* const scr, const __nv_bfloat16* __restrict__ xin,
                const __nv_bfloat16* __restrict__ shift_k, const __nv_bfloat16* __restrict__ ssm_D, __nv_bfloat16* __restrict__ outp,
                const __nv_bfloat16* __restrict__ w_gate, const __nv_bfloat16* __restrict__ w_up, const __nv_bfloat16* __restrict__ w_down,
                const __grid_constant__ Params prm) {
    extern __shared__ __align__(1024) unsigned char smem[];
    const uint32_t smb = SM0 + ((blockIdx.x & 1) << 24);
    const uint32_t bar = smb + OFF_BAR;
    const int tid = threadIdx.x, lane = tid & 31;
    const int warp = __shfl_sync(0xffffffffu, tid >> 5, 0);
    const int rank = blockIdx.x & 1;
    int P;
    {
        const int cl = blockIdx.x >> 1, t = cl - 4, u = t - 32, d = (u * 37) >> 8;
        const int pa = (t & 7) * 8 + (t >> 3), pb = (1 + u - 7 * d) * 8 + 4 + d;
        P = (cl < 4 ? cl + 4 : (t < 32 ? pa : pb)) & 63;
    }
    const int L = 2 * P + rank;
    const int rr = 2 * (P >> 3) + rank;
    const int jj = P & 7;
    const int R2 = rr + 16 * (jj >> 2), cN = jj & 3;

    uint4 hk[4];
    const int role = warp | ((blockIdx.x >> 4) & 8);
    const __nv_bfloat16* taps = ssm_k + (size_t)(4 * L + 2 * ((warp >> 2) & 1)) * S_ + (tid & 127) * 8;
    auto load_taps = [&](int i) {
        asm volatile("{ .reg .pred p; setp.lt.s32 p, %5, 8; @p ld.global.nc.L1::no_allocate.v4.u32 {%0, %1, %2, %3}, [%4]; }"
                     : "=r"(hk[i].x), "=r"(hk[i].y), "=r"(hk[i].z), "=r"(hk[i].w) : "l"(taps + i * 1024), "r"(role));
    };
    hk[0] = ldg128(role < 8 ? taps : shift_k + (8 * P + 2 * (lane >> 3)) * 4);
    load_taps(2); load_taps(1); load_taps(3);
    uint32_t pre;
    asm volatile("ld.relaxed.gpu.global.u32 %0, [%1];" : "=r"(pre) : "l"(warp < 8 ? (const void*)(ssm_D + 4 * L + 2 * (warp >> 2)) : (const void*)&scr->epoch[blockIdx.x]) : "memory");
    if (blockIdx.x < NCTA) {
        if (warp >= 8 && warp < 15 && elect_one()) asm volatile("prefetch.tensormap [%0];" ::"l"(&prm.k + (warp & 7)) : "memory");
        if (warp == 15) {
            if (elect_one()) {
#pragma unroll
                for (int i = 0; i < 14; i++) mbar_init(bar + 8 * i, 1);
            }
            __syncwarp();
            if (lane < 14) mbar_expect(bar + 8 * lane, lane < 8 ? 4224 : lane < 12 ? 8192 : 4096);
            __syncwarp();
            if (elect_one()) {
                tma3(smb + OFF_K, &prm.k, 8 * P, 32 * rank - 1, 0, bar);
                tma3(smb + OFF_V, &prm.v, 8 * P, 32 * rank - 1, 0, bar);
                bulk_ld(smb + OFF_XR, xin + (size_t)L * 8 * D_, 8192, bar + 8 * B_XR);
            }
            __syncwarp();
        }
        if (elect_one()) {
            const uint32_t b0 = bar + 8 * warp;
            const bool lo = warp < 8;
            mbar_init(b0 + 128, lo ? 5 : 9);
            mbar_init(b0 + 256, lo ? 1 : 4);
            mbar_init(b0 + 384, warp == B_OVW - 48 ? 2 : 1);
            mbar_init(b0 + 512, 1);
            mbar_init(b0 + 640, 16);
            mbar_init(b0 + 768, 1);
            mbar_init(b0 + 896, 1);
            mbar_init(b0 + 1024, 1);
            mbar_init(b0 + 1152, 1);
            mbar_init(b0 + 1280, 1);
            mbar_expect(b0 + 1024, 16384);
            mbar_expect(b0 + 1152, 16384);
            mbar_expect(b0 + 1280, lo ? 16384 : 12288);
            mbar_expect(b0 + 128, lo ? 2048 : 1024);
            mbar_expect(b0 + 768, warp == 15 ? 4096 : 8192);
            if (lo) { mbar_expect(b0 + 256, 8192); mbar_expect(b0 + 384, 8192); mbar_expect(b0 + 896, 6144); }
            asm volatile("fence.mbarrier_init.release.cluster;" ::: "memory");
        }
        __syncwarp();
        cluster_arrive();

        if (warp < 8) {
            asm volatile("setmaxnreg.inc.sync.aligned.u32 192;");
            const int wg = warp >> 2, w = warp & 3, g = lane >> 2, q = lane & 3, t128 = tid & 127;
            {
                const uint32_t ht = smb + OFF_H + 2 * wg * HT;
                {
                    uint4(&v)[4] = hk;
                    if (t128 < 16) sts128(ht + (t128 >> 2) * 2112 + (t128 & 3) * 16, make_uint4(0, 0, 0, 0));
                    else if (t128 < 24) sts128(smb + OFF_U + (2 * wg + ((t128 >> 2) & 1)) * UT + (t128 & 3) * 16, make_uint4(0, 0, 0, 0));
                    if (t128 == 0) {
                        const uint32_t dd = pre;
                        v[0].x = (v[0].x & 0xffff0000u) | (pack2(bf_lo(v[0].x) + bf_lo(dd), 0.f) & 0xffffu);
                        v[2].x = (v[2].x & 0xffff0000u) | (pack2(bf_lo(v[2].x) + bf_hi(dd), 0.f) & 0xffffu);
                    }
#pragma unroll
                    for (int i = 0; i < 4; i++) sts128(ht + (i >> 1) * HT + (t128 & 1) * 2112 + (4 + (i & 1) * 64 + (t128 >> 1)) * 16, v[i]);
                    asm volatile("fence.proxy.async.shared::cta;" ::: "memory");
                }
                cluster_wait();
                nb_sync(NB_WG + wg, 128);

                const int sig = g >> 1, lam = 2 * w + (g & 1) - 2 * q;
                const uint32_t base1 = smb + OFF_U + 2 * wg * UT + (24 + sig * 72 + lam) * 4;
                const uint32_t base0 = base1 - (lam < 0 ? 32 : 0);
                const uint64_t db0 = mkdesc(ht + 64, 2112, 128, 0), db1 = db0 + (HT >> 4);
                const bool s0 = sig & 1, s1 = sig >> 1, d0 = s0 && q >= 2;
                const uint32_t yoff = OFF_V + (2 * rank + wg) * 512 + (32 * w + (lane ^ w)) * 4;
                float acc0[64], acc1[64];
                uint32_t hs[2] = {0, 0}, hz[4] = {0, 0, 0, 0};
                uint32_t a0[16], a1[16];

                auto load = [&](auto Ic, uint32_t(&a)[16], int c) {
                    constexpr int I = decltype(Ic)::value;
                    const uint32_t o = c * UT + I * 4 * 72 * 4;
                    uint32_t p[9];
                    p[0] = lds32(base1 + o - 64);
                    p[1] = lds32(base0 + o);
#pragma unroll
                    for (int m = 1; m < 8; m++) p[m + 1] = lds32(base1 + o + 32 * m);
#pragma unroll
                    for (int t = 0; t < 4; t++) { a[4 * t] = p[2 * t + 1]; a[4 * t + 1] = p[2 * t + 2]; a[4 * t + 2] = p[2 * t]; a[4 * t + 3] = p[2 * t + 1]; }
                };
                auto mma = [&](auto Ic, float* acc, uint32_t(&a)[16], uint64_t db) {
                    constexpr int I = decltype(Ic)::value;
                    WFENCE;
#pragma unroll
                    for (int t = 0; t < 4; t++) {
                        if (I == 0 && t == 0) WG<128>::template rs0<0>(acc, a[0], a[1], a[2], a[3], db);
                        else WG<128 - 16 * I>::template rs<0>(acc + 8 * I, a[4 * t], a[4 * t + 1], a[4 * t + 2], a[4 * t + 3], db - t);
                    }
                    WCOMMIT;
                };
                auto red = [&](auto Ic) {
                    constexpr int I = decltype(Ic)::value;
                    uint32_t z[8], sm[2][2];
#pragma unroll
                    for (int e = 0; e < 8; e++) z[e] = pack2(acc0[8 * I + e], acc1[8 * I + e]);
#pragma unroll
                    for (int J = 0; J < 2; J++)
#pragma unroll
                        for (int ro = 0; ro < 2; ro++) {
                            const uint32_t z0 = d0 ? (J ? z[2 * ro] : hz[2 * ro]) : z[4 * J + 2 * ro];
                            const uint32_t z1 = d0 ? (J ? z[2 * ro + 1] : hz[2 * ro + 1]) : z[4 * J + 2 * ro + 1];
                            sm[J][ro] = hadd2(s0 ? z1 : z0, __shfl_xor_sync(0xffffffffu, s0 ? z0 : z1, 10));
                        }
                    const uint32_t r0 = hadd2(s1 ? hs[1] : sm[0][0], __shfl_xor_sync(0xffffffffu, s1 ? hs[0] : sm[0][1], 16));
                    const uint32_t r1 = hadd2(s1 ? sm[0][1] : sm[1][0], __shfl_xor_sync(0xffffffffu, s1 ? sm[0][0] : sm[1][1], 16));
                    hs[0] = sm[1][0]; hs[1] = sm[1][1];
#pragma unroll
                    for (int e = 0; e < 4; e++) hz[e] = z[4 + e];
                    stasync32((smb ^ (1u << 24)) + yoff + I * KVP, rank ? r0 : r1, (bar ^ (1u << 24)) + 8 * (B_Y + I));
                    asm volatile("st.shared.u32 [%0], %1;" ::"r"(smb + yoff + I * KVP), "r"(rank ? r1 : r0) : "memory");
                    __syncwarp();
                    mbar_arrive_if(bar + 8 * (B_Y + I), lane == 0);
                };
                auto step = [&](auto Ic) {
                    constexpr int I = decltype(Ic)::value;
                    if constexpr (I < 7) mbar_wait(bar + 8 * (B_U + I + 1), 0);
                    WWAIT(1);
                    rename<8 * I, 64>(acc0);
                    if constexpr (I < 7) { load(IC<I + 1>{}, a0, 0); mma(IC<I + 1>{}, acc0, a0, db0); }
                    if constexpr (I < 7) WWAIT(1); else WWAIT(0);
                    rename<8 * I, 64>(acc1);
                    if constexpr (I < 7) load(IC<I + 1>{}, a1, 1);
                    red(Ic);
                    if constexpr (I < 7) mma(IC<I + 1>{}, acc1, a1, db1);
                };
                mbar_wait(bar + 8 * B_U, 0);
                load(IC<0>{}, a0, 0); mma(IC<0>{}, acc0, a0, db0);
                load(IC<0>{}, a1, 1); mma(IC<0>{}, acc1, a1, db1);
                step(IC<0>{}); step(IC<1>{}); step(IC<2>{}); step(IC<3>{});
                step(IC<4>{}); step(IC<5>{}); step(IC<6>{}); step(IC<7>{});
            }
            mbar_wait(bar + 8 * B_FW, 0);
            if (wg) mbar_wait(bar + 8 * B_OVW, 0);
            asm volatile("setmaxnreg.inc.sync.aligned.u32 224;");
            constexpr uint64_t dw = mkdesc(SM0 + OFF_W, 8192, 1024, 1);
            uint32_t hv[32];
            auto load_res = [&](int i0, int i1) {
                const uint32_t* hp = (const uint32_t*)(scr->h + ((size_t)R2 * 64 + 16 * cN) * 64 + 16 * w + g) + q;
#pragma unroll
                for (int i = i0; i < i1; i++) asm volatile("ld.relaxed.gpu.global.u32 %0, [%1];" : "=r"(hv[i]) : "l"(hp + (i >> 1) * 256 + (i & 1) * 32) : "memory");
            };
            const uint32_t ewb = SM0 + OFF_BAR + 8 * B_EW + ((lane & 1) << 24);
            {
                uint32_t a[128];
                const uint32_t stat = smb + OFF_STAT + (wg * 64 + 16 * w + g) * 4;
                uint32_t* const hh = (uint32_t*)(scr->hh + ((size_t)(rr + 16 * wg) * 176 + 22 * jj) * 64 + 16 * w + g) + q;
                auto mainloop = [&](auto Cc, float* acc) {
                    constexpr int C = decltype(Cc)::value;
                    const uint32_t fa = bar + 8 * (wg ? B_FL : B_FA);
                    const uint32_t la = smb + OFF_A + (lane >> 4) * 1024 + (16 * w + (lane & 15)) * 16;
                    const uint64_t odd = (jj & 1) * 2;
                    uint32_t nm[2];
                    auto ldf = [&](int s, int ks) {
                        uint32_t* f = a + 16 * s + 4 * ks;
                        asm volatile("ldmatrix.sync.aligned.m8n8.x4.shared.b16 {%0, %1, %2, %3}, [%4];"
                                     : "=r"(f[0]), "=r"(f[1]), "=r"(f[2]), "=r"(f[3]) : "r"(la + s * 8192 + ks * 2048) : "memory");
                    };
                    auto lda = [&](int s) {
                        mbar_wait(fa + 8 * s, 0);
#pragma unroll
                        for (int ks = 0; ks < 4; ks++) ldf(s, ks);
                    };
                    auto center = [&](int s) {
#pragma unroll
                        for (int i = 0; i < 16; i++) asm volatile("add.rn.bf16x2 %0, %0, %1;" : "+r"(a[16 * s + i]) : "r"(nm[i & 1]));
                        if (lane == 0) mbar_arrive(bar + 8 * (B_EA + s));
                    };
                    if constexpr (C > 0) mbar_wait(bar + 8 * (B_FW + 8 * C), 0);
                    if constexpr (C == 0) {
                        const float2* sp = scr->sth + (rr + 16 * wg) * 512 + q * 64 + 16 * w + g;
                        float2 v[4];
                        mbar_wait(bar + 8 * (B_FG + wg), 0);
#pragma unroll
                        for (int i = 0; i < 4; i++) asm volatile("ld.relaxed.gpu.global.v2.f32 {%0, %1}, [%2];" : "=f"(v[i].x), "=f"(v[i].y) : "l"(sp + (i >> 1) * 8 + (i & 1) * 256) : "memory");
                        lda(0); lda(1);
                        float z[4] = {v[0].x + v[1].x, v[2].x + v[3].x, v[0].y + v[1].y, v[2].y + v[3].y};
#pragma unroll
                        for (int o = 1; o < 4; o <<= 1)
#pragma unroll
                            for (int i = 0; i < 4; i++) z[i] += __shfl_xor_sync(0xffffffffu, z[i], o);
#pragma unroll
                        for (int r = 0; r < 2; r++) {
                            const float mean = z[r] * (1.f / D_);
                            nm[r] = pack2(-mean, -mean);
                            const float rs = rsqrtf(fmaxf(fmaf(-mean, mean, z[2 + r] * (1.f / D_)), 0.f) + LN_EPS);
                            asm volatile("st.shared.f32 [%0], %1;" ::"r"(stat + r * 32), "f"(rs) : "memory");
                        }
                        center(0);
                        mbar_wait(fa + 16, 0);
                    }
                    if (C > 0 || wg) nb_sync(NB_T0 + wg, 256);
#pragma unroll
                    for (int s = 0; s < 8; s++) {
                        const int n = 8 * C + s;
                        uint32_t ok = 1, oka = 1;
                        WFENCE;
#pragma unroll
                        for (int ks = 0; ks < 4; ks++) {
                            const uint32_t* f = a + 16 * s + 4 * ks;
                            const uint64_t db = dw + (n % NW) * 1024 + ks * 128;
                            if (ks == 1 && s < 7) ok = mbar_test(bar + 8 * (B_FW + n + 1), 0);
                            if (ks == 2 && C == 0 && s < 5) oka = mbar_test(fa + 8 * (s + 3), 0);
                            if (ks == 3 && s == 7 && !(G2_AFTER && C == 2 && wg)) nb_arrive(NB_T0 + (wg ^ 1), 256);
                            if constexpr (C < 2) {
                                if (s == 0 && ks == 0) WG<128>::template rs0<1>(acc, f[0], f[1], f[2], f[3], db);
                                else WG<128>::template rs<1>(acc, f[0], f[1], f[2], f[3], db);
                            } else if (s == 0 && ks == 0) {
                                WG<48>::template rs0<1>(acc, f[0], f[1], f[2], f[3], db + odd);
                                WG<48>::template rs0<1>(acc + 32, f[0], f[1], f[2], f[3], db + 512 + odd);
                            } else {
                                WG<48>::template rs<1>(acc, f[0], f[1], f[2], f[3], db + odd);
                                WG<48>::template rs<1>(acc + 32, f[0], f[1], f[2], f[3], db + 512 + odd);
                            }
                            if (C == 0 && s < 6) ldf(s + 2, ks);
                        }
                        WCOMMIT;
                        if (C == 0 && s < 7) center(s + 1);
                        if (s > 0) { WWAIT(1); if (lane < 2) mbar_arrive_cl(ewb + 8 * ((n + NW - 1) % NW)); }
                        if (!ok) mbar_wait(bar + 8 * (B_FW + n + 1), 0);
                        if (!oka) mbar_wait(fa + 8 * (s + 3), 0);
                    }
                    WWAIT(0);
                    if (lane < 2) mbar_arrive_cl(ewb + 8 * ((8 * C + 7) % NW));
                    if constexpr (C < 2) rename<0, 64>(acc); else { rename<0, 24>(acc); rename<32, 56>(acc); }
                };
                auto epilogue = [&](const float* acc, auto Cc) {
                    constexpr int c = decltype(Cc)::value;
                    float c0[2], c1[2], kk[2];
#pragma unroll
                    for (int r = 0; r < 2; r++) {
                        const float rs = __uint_as_float(lds32(stat + r * 32)), r2 = rs * rs;
                        c0[r] = 0.7978845608028654f * rs;
                        c1[r] = (0.7978845608028654f * 0.044715f) * rs * r2;
                        kk[r] = 0.5f * r2;
                    }
                    uint32_t* dst = hh + chunk_grp(jj, c) * 256;
                    uint32_t prev[2] = {0, 0};
                    const uint32_t zero = __float_as_uint(kk[0]) >> 31;
                    if (c < 2) geglu_store<0, 8, PACE>(acc, acc + 32, c0, c1, kk, dst, zero, prev);
                    else if (wg == 0) geglu_store<0, 6, PACE2>(acc, acc + 32, c0, c1, kk, dst, zero, prev);
                    else {
                        geglu_store<0, G2_AFTER, PACE3>(acc, acc + 32, c0, c1, kk, dst, zero, prev);
                        if (G2_AFTER) nb_arrive(NB_T0, 256);
                        geglu_store<G2_AFTER, 6, PACE3>(acc, acc + 32, c0, c1, kk, dst, zero, prev);
                    }
                    nb_arrive(NB_HH + c, 288);
                };
                { float acc[64]; mainloop(IC<0>{}, acc); epilogue(acc, IC<0>{}); }
                { float acc[64]; mainloop(IC<1>{}, acc); epilogue(acc, IC<1>{}); }
                {
                    float acc[64];
                    if (wg == 0) load_res(0, RES_EARLY);
                    mainloop(IC<2>{}, acc);
                    if (wg == 0) load_res(RES_EARLY, 32);
                    epilogue(acc, IC<2>{});
                }
            }
            if (wg == 0) {
                float acc[64];
#pragma unroll
                for (int i = 0; i < 64; i++) asm volatile("mov.b32 %0, 0;" : "=f"(acc[i]));
                const uint32_t peer = bar ^ (1u << 24);
                const uint32_t stg = smb + OFF_W + 8 * 16384 + w * 4096;
                const int mat = lane >> 3, l7 = lane & 7;
                uint32_t sa[4], sl[2];
#pragma unroll
                for (int k = 0; k < 4; k++) sa[k] = stg + ((mat & 1) * 8 + l7) * 128 + (((2 * k + (mat >> 1)) ^ l7) << 4);
#pragma unroll
                for (int k = 0; k < 2; k++) sl[k] = stg + (4 * k + mat) * 128 + ((l7 ^ (4 * k + mat)) << 4);
                __nv_bfloat16* op = outp + (size_t)(64 * R2 + 16 * w + mat) * D_ + 128 * cN + 8 * l7;
                asm volatile("" : "+r"(sa[0]), "+r"(sa[1]), "+r"(sa[2]), "+r"(sa[3]), "+r"(sl[0]), "+r"(sl[1]), "+l"(op));
                mbar_wait(bar + 8 * B_G2, 0);
                mbar_wait(bar + 8 * (B_FW + 24), 0);
                nb_sync(NB_T0, 256);
                constexpr uint64_t da0 = mkdesc(SM0 + OFF_A, 1024, 128, 0);
                uint32_t ws = 24 % NW, pw = 0, pa = bar + 8 * B_EA, ln = lane;
                asm volatile("" : "+r"(ln));
                auto piece = [&](auto Kc, int p) {
                    constexpr int KS = decltype(Kc)::value;
                    const uint64_t da = da0 + (p & 7) * 512, db = dw + ws * 1024;
                    const uint32_t cw = ws;
                    if (++ws == NW) ws = 0;
                    WFENCE;
                    WG<128>::template ss<0, 1>(acc, da, db);
                    const uint32_t nb = bar + 8 * (B_G2 + (KS != 3 ? p + 1 : min(p + 1, 23))), ok = mbar_test(nb, 0);
                    const uint32_t okw = mbar_test(nb + 8 * (B_FW + 24 - B_G2), 0);
#pragma unroll
                    for (int ks = 1; ks < KS; ks++) WG<128>::template ss<0, 1>(acc, da + ks * 128, db + ks * 128);
                    WCOMMIT;
                    WWAIT(1);
                    if (KS == 4) {
                        const bool rel = p > 0 && p <= 24 - NW && ln < 2;
                        mbar_arrive_if(bar + 8 * (B_EW + pw), rel);
                        mbar_arrive_cl_if(peer + 8 * (B_EW + pw), rel);
                    }
                    mbar_arrive_if(pa, p > 0 && ln == 0);
                    pa = bar + 8 * (B_EA + (p & 7));
                    pw = cw;
                    if (!okw) mbar_wait(nb + 8 * (B_FW + 24 - B_G2), 0);
                    if (!ok) mbar_wait(nb, 0);
                };
#pragma unroll 1
                for (int p = 0; p < 15; p++) piece(IC<4>{}, p);
                piece(IC<2>{}, 15);
#pragma unroll 1
                for (int p = 16; p < 24; p++) piece(IC<3>{}, p);
                WWAIT(0);
                rename<0, 64>(acc);
#pragma unroll
                for (int b = 0; b < 2; b++) {
#pragma unroll
                    for (int j = 8 * b; j < 8 * b + 8; j += 2) {
                        asm volatile("stmatrix.sync.aligned.m8n8.x4.shared.b16 [%0], {%1, %2, %3, %4};" ::"r"(sa[(j >> 1) & 3] + b * 2048),
                                     "r"(hadd2(pack2(acc[4 * j], acc[4 * j + 1]), hv[2 * j])), "r"(hadd2(pack2(acc[4 * j + 2], acc[4 * j + 3]), hv[2 * j + 1])),
                                     "r"(hadd2(pack2(acc[4 * j + 4], acc[4 * j + 5]), hv[2 * j + 2])), "r"(hadd2(pack2(acc[4 * j + 6], acc[4 * j + 7]), hv[2 * j + 3])) : "memory");
                    }
                    __syncwarp();
#pragma unroll
                    for (int it = 0; it < 4; it++) {
                        const uint4 o = lds128(sl[it & 1] + b * 2048 + (it >> 1) * 1024);
                        asm volatile("st.global.v4.u32 [%0], {%1, %2, %3, %4};" ::"l"(op + 4 * it * D_ + 64 * b), "r"(o.x), "r"(o.y), "r"(o.z), "r"(o.w) : "memory");
                    }
                }
            }
        } else {
            asm volatile("setmaxnreg.dec.sync.aligned.u32 64;");
            if (warp < 12) {
                const int p = lane >> 3, l = 8 * (warp - 8) + (lane & 7);
                const bool loc = (p >> 1) == rank;
                const uint4 sk = hk[0];
                const uint32_t w0 = __byte_perm(sk.x, sk.z, 0x5410), w1 = __byte_perm(sk.x, sk.z, 0x7632);
                const uint32_t w2 = __byte_perm(sk.y, sk.w, 0x5410), w3 = __byte_perm(sk.y, sk.w, 0x7632);
                const uint32_t dcta = SM0 + ((p >> 1) << 24);
                uint32_t src = smb + OFF_K + l * 16 + p * 4;
                uint32_t dst = dcta + OFF_U + (p & 1) * 2 * UT + (24 + 144 * rank + 4 * l + 8 * (l >> 4)) * 4;
                uint32_t ub = dcta + OFF_BAR + 8 * B_U;
                cluster_wait();
                nb_sync(NB_U, 128);
#pragma unroll 1
                for (int i = 0; i < 8; i++) {
                    mbar_wait(bar + 8 * (B_KV + i), 0);
                    uint32_t kr[8], u[5];
#pragma unroll
                    for (int r = 0; r < 8; r++) kr[r] = lds32(src + (r & 3) * 528 + (r >> 2) * 16);
#pragma unroll
                    for (int r = 0; r < 5; r++) u[r] = lds32(src + 8 * KVP + ((r + 3) & 3) * 528 + ((r + 3) >> 2) * 16);
#pragma unroll
                    for (int r = 0; r < 5; r++) u[r] = hmul2(hfma2(kr[r + 3], w0, hfma2(kr[r + 2], w1, hfma2(kr[r + 1], w2, hmul2(kr[r], w3)))), u[r]);
                    const uint4 t0 = make_uint4(__byte_perm(u[1], u[0], 0x5410), __byte_perm(u[2], u[1], 0x5410), __byte_perm(u[3], u[2], 0x5410), __byte_perm(u[4], u[3], 0x5410));
                    const uint4 t1 = make_uint4(__byte_perm(u[1], u[0], 0x7632), __byte_perm(u[2], u[1], 0x7632), __byte_perm(u[3], u[2], 0x7632), __byte_perm(u[4], u[3], 0x7632));
                    if (loc) { sts128(dst, t0); sts128(dst + UT, t1); }
                    else { stasync128(dst, t0.x, t0.y, t0.z, t0.w, ub); stasync128(dst + UT, t1.x, t1.y, t1.z, t1.w, ub); }
                    __syncwarp();
                    mbar_arrive_if(bar + 8 * (B_U + i), lane == 0);
                    if (warp == 8 + (i & 3) && elect_one()) {
                        const int n = i + KV_AHEAD;
                        if (n < 8) {
                            tma3(smb + OFF_K + n * KVP, &prm.k, 8 * P, 64 * n + 32 * rank - 1, 0, bar + 8 * (B_KV + n));
                            tma3(smb + OFF_V + n * KVP, &prm.v, 8 * P, 64 * n + 32 * rank - 1, 0, bar + 8 * (B_KV + n));
                        }
                        if (i == X_AT || i == X2_AT) tma3(smb + OFF_X + (i == X_AT ? 0 : 8192), &prm.x, 8 * P, 128 * rank, i == X_AT ? 0 : 4, bar + 8 * (B_X + (i != X_AT)));
                        if (i == G_AT || i == GL_AT) bulk_ld(smb + OFF_SX + (i == G_AT ? 0 : 4096), scr->stx + rank * 1024 + (i == G_AT ? 0 : 512), 4096, bar + 8 * (B_SX + (i != G_AT)));
                        if (i >= W_AT && i < W_AT + PRE / 2) {
#pragma unroll 1
                            for (int s = 2 * (i - W_AT); s < 2 * (i - W_AT) + 2; s++)
                                tma2_mc(smb + OFF_W + s * 16384 + rank * 8192, rank ? &prm.wu : &prm.wg, 176 * jj + 48 * (jj & 1), 64 * s, bar + 8 * (B_FW + s));
                        }
                    }
                    src += KVP;
                    dst += 288 * 4;
                    ub += 8;
                }
            } else {
                const int ew = warp - 12, t = tid & 127;
                if (ew == 3) {
                    if (elect_one()) {
#pragma unroll 1
                        for (int i = 1; i < KV_AHEAD; i++) {
                            tma3(smb + OFF_K + i * KVP, &prm.k, 8 * P, 64 * i + 32 * rank - 1, 0, bar + 8 * (B_KV + i));
                            tma3(smb + OFF_V + i * KVP, &prm.v, 8 * P, 64 * i + 32 * rank - 1, 0, bar + 8 * (B_KV + i));
                            if (i == XL_AT) bulk_ld(smb + OFF_XR + 8192, xin + (size_t)(1024 + L * 8) * D_, 8192, bar + 8 * (B_XR + 1));
                        }
                    }
                    __syncwarp();
                }
                cluster_wait();
                const unsigned ep = pre + 1;
                const uint32_t tag = ep & 0xffff;
                uint32_t zc = 0;
#pragma unroll 1
                for (int hb = 0; hb < 2; hb++) {
                    float s = 0.f, ss = 0.f;
                    mbar_wait(bar + 8 * (B_XR + hb), 0);
                    {
                        uint4 xq[4];
#pragma unroll
                        for (int i = 0; i < 4; i++) xq[i] = lds128(smb + OFF_XR + hb * 8192 + (t >> 4) * 1024 + (t & 15) * 16 + i * 256);
#pragma unroll
                        for (int i = 0; i < 4; i++) {
                            const uint32_t wv[4] = {xq[i].x, xq[i].y, xq[i].z, xq[i].w};
#pragma unroll
                            for (int p = 0; p < 4; p++) { const float a = bf_lo(wv[p]), b = bf_hi(wv[p]); s += a + b; ss = fmaf(a, a, fmaf(b, b, ss)); }
                        }
                    }
                    float z = ((lane & 8) ? ss : s) + __shfl_xor_sync(0xffffffffu, (lane & 8) ? s : ss, 8);
                    z = (z + __shfl_xor_sync(0xffffffffu, z, 1)) + (__shfl_xor_sync(0xffffffffu, z, 2) + __shfl_xor_sync(0xffffffffu, z, 3));
                    const float mean = (z + __shfl_xor_sync(0xffffffffu, z, 4)) * (1.f / D_);
                    const float msq = (__shfl_xor_sync(0xffffffffu, z, 8) + __shfl_xor_sync(0xffffffffu, z, 12)) * (1.f / D_);
                    const float rs = rsqrtf(fmaxf(fmaf(-mean, mean, msq), 0.f) + LN_EPS);
                    if ((t & 15) == 0)
                        asm volatile("st.relaxed.gpu.global.v2.u32 [%0], {%1, %2};" ::"l"(scr->stx + ((L >> 4) & 1) * 1024 + ((L >> 5) + 4 * hb) * 128 + (L & 15) * 8 + (t >> 4)),
                                     "r"(pack2(0.f, -mean) | tag), "r"(pack2(0.f, rs) | tag) : "memory");
                    if (hb == 0) asm volatile("ld.relaxed.gpu.global.u32 %0, [%1];" : "=r"(zc) : "l"(&scr->cnt[(C_Z + (L & 15)) * 32]) : "memory");
                }
                const int ws_ = (t >> 1) & 3, sg = ((t >> 4) & 1) + ((t >> 2) & 2);
                uint32_t ya = smb + OFF_V + (32 * ws_ + ((4 * (2 * sg + (t & 1)) + ((t >> 5) ^ (2 * (sg & 1)))) ^ ws_)) * 4;
                const int tok = 128 * rank + t;
                uint4* hp = scr->h + ((tok >> 6) * 64 + P) * 64 + (tok & 63);
                float2* sp = scr->sth + (tok >> 6) * 512 + (P & 7) * 64 + (tok & 63);
                unsigned* cp = &scr->cnt[(C_H + 16 + 4 * ((lane >> 1) & 3) + 2 * rank + (lane & 1)) * 32];
                asm volatile("" : "+l"(cp));
                mbar_wait(bar + 8 * B_X, 0);
                uint4 xq = lds128(smb + OFF_X + t * 16);
                mbar_wait(bar + 8 * B_SX, 0);
                uint32_t yw[4] = {0, 0, 0, 0}, ok = 0, okn = mbar_test(bar + 8 * (B_Y + 1), 0);
                auto ldy = [&](uint32_t a, uint32_t c) {
                    asm volatile("{ .reg .pred p; setp.ne.u32 p, %5, 0;\n @p ld.volatile.shared.u32 %0, [%4];\n @p ld.volatile.shared.u32 %1, [%4 + 512];\n"
                                 " @p ld.volatile.shared.u32 %2, [%4 + 1024];\n @p ld.volatile.shared.u32 %3, [%4 + 1536]; }"
                                 : "+r"(yw[0]), "+r"(yw[1]), "+r"(yw[2]), "+r"(yw[3]) : "r"(a), "r"(c) : "memory");
                };
                uint2 st = lds64(smb + OFF_SX + t * 8);
                if (__any_sync(0xffffffffu, (int)(zc - ep * 4) < 0)) { if (lane == 0) poll_ge(&scr->cnt[(C_Z + (L & 15)) * 32], ep * 4); __syncwarp(); }
                asm volatile("fence.acquire.gpu;" ::: "memory");
#pragma unroll
                for (int i = 0; i < 8; i++) {
                    for (uint32_t n = 0; __any_sync(0xffffffffu, ((st.x ^ tag) | (st.y ^ tag)) & 0xffff); n++) {
                        asm volatile("ld.relaxed.gpu.global.v2.u32 {%0, %1}, [%2];" : "=r"(st.x), "=r"(st.y) : "l"(scr->stx + rank * 1024 + i * 128 + t) : "memory");
                        if (n > 4000000u) __trap();
                    }
                    const uint32_t xw[4] = {xq.x, xq.y, xq.z, xq.w};
                    uint32_t hw[4];
#pragma unroll
                    for (int p = 0; p < 4; p++) hw[p] = hmul2(hadd2(xw[p], __byte_perm(st.x, 0, 0x3232)), __byte_perm(st.y, 0, 0x3232));
                    if (!ok) { mbar_wait(bar + 8 * (B_Y + i), 0); ldy(ya, 1); }
#pragma unroll
                    for (int p = 0; p < 4; p++) hw[p] = hfma2(hw[p], yw[p], xw[p]);
                    auto fetch = [&]() {
                        ok = okn;
                        ldy(ya + KVP, ok);
                        if (i < 6) okn = mbar_test(bar + 8 * (B_Y + i + 2), 0);
                        asm volatile("ld.volatile.shared.v2.u32 {%0, %1}, [%2];" : "=r"(st.x), "=r"(st.y) : "r"(smb + OFF_SX + (i + 1) * 1024 + t * 8) : "memory");
                        asm volatile("ld.volatile.shared.v4.u32 {%0, %1, %2, %3}, [%4];" : "=r"(xq.x), "=r"(xq.y), "=r"(xq.z), "=r"(xq.w) : "r"(smb + OFF_X + (i + 1) * 2048 + t * 16) : "memory");
                    };
                    if (i < 7 && i != 3) fetch();
                    asm volatile("st.global.v4.u32 [%0], {%1, %2, %3, %4};" ::"l"(hp), "r"(hw[0]), "r"(hw[1]), "r"(hw[2]), "r"(hw[3]) : "memory");
                    float s = 0.f, ss = 0.f;
#pragma unroll
                    for (int p = 0; p < 4; p++) {
                        const float h0 = bf_lo(hw[p]), h1 = bf_hi(hw[p]);
                        s += h0 + h1;
                        ss = fmaf(h0, h0, fmaf(h1, h1, ss));
                    }
                    asm volatile("red.relaxed.gpu.global.add.v2.f32 [%0], {%1, %2};" ::"l"(sp), "f"(s), "f"(ss) : "memory");
                    if (i == 3) {
                        nb_arrive(NB_R, 160);
                        mbar_wait(bar + 8 * (B_X + 1), 0);
                        mbar_wait(bar + 8 * (B_SX + 1), 0);
                        fetch();
                    }
                    ya += KVP;
                    hp += 4 * 4096;
                    sp += 4 * 512;
                }
                nb_sync(NB_E, 128);
                mbar_arrive_if(bar + 8 * B_OVL, t == 32);
                if (ew == 0) {
                    fence_gpu();
                    if (lane < 8) red_add(cp);
                    mbar_arrive_cl_if(SM0 + OFF_BAR + 8 * B_OVW + (lane << 24), lane < 2);
                }
                __syncwarp();
            }
            asm volatile("setmaxnreg.dec.sync.aligned.u32 32;");
            const int par = (warp >> 2) & 1;
            if ((warp & 3) == 0) {
                if (elect_one()) {
                    if (mapa((uint32_t)__cvta_generic_to_shared(smem), rank) != smb || mapa(smb, rank ^ 1) != (smb ^ (1u << 24))) __trap();
                    static_assert(PRE % 2 == 0 && NW % 2 == 0, "");
                    uint32_t ws = PRE + par, wp = 1, fb = bar + 8 * (B_FW + PRE + par);
                    mbar_wait(bar + 8 * B_OVW, 0);
                    mbar_wait(bar + 8 * (B_FA + W_AFTER), 0);
                    auto slot = [&](const CUtensorMap* m, int x, int y, int depth) {
                        mbar_wait(bar + 8 * (B_EW + ws), wp);
                        if (depth < NW) mbar_wait(fb - 8 * depth, 0);
                        tma2_mc(smb + OFF_W + ws * 16384 + rank * 8192, m, x, y, fb);
                        fb += 16;
                        ws += 2;
                        if (ws >= NW) { ws -= NW; wp ^= 1; }
                    };
#pragma unroll 1
                    for (int c = 0; c < 3; c++) {
                        const int x0 = 176 * jj + ((jj & 1) ? (c == 2 ? -16 : 48 + 64 * c) : 64 * c);
                        if (c == 1) mbar_wait(bar + 8 * (B_FL + WL_AFTER), 0);
#pragma unroll 1
                        for (int s = (c ? 0 : PRE) + par; s < 8; s += 2) slot(rank ? &prm.wu : &prm.wg, x0, 64 * s, NW);
                    }
#pragma unroll 1
                    for (int c = 0; c < 3; c++) {
                        const CUtensorMap* m = c < 2 ? &prm.wd : &prm.wd48;
#pragma unroll 1
                        for (int y = 176 * par + 8 * chunk_grp(par, c); y < 1408; y += 352) slot(m, 128 * cN + 64 * rank, y, DW2);
                    }
                }
            } else if ((warp & 3) == 1) {
                if (elect_one()) {
#pragma unroll 1
                    for (int c = 0; c < 5; c++) {
                        const uint4* src = c < 2 ? scr->h + (rr + 16 * c) * 4096 + (2 + par) * 512 : scr->hh + (R2 * 176 + 22 * (2 + par) + chunk_grp(par, c - 2)) * 64;
                        const uint32_t step = c < 2 ? 1024 : 44 * 64, bytes = c < 4 ? 8192 : 6144;
                        uint32_t fb = bar + 8 * ((c == 0 ? B_FA : c == 1 ? B_FL : B_G2 + 8 * (c - 2)) + 2 + par);
                        mbar_wait(bar + 8 * (B_FG + c), 0);
                        asm volatile("fence.proxy.async.global;" ::: "memory");
#pragma unroll 1
                        for (int s = 2 + par; s < 8; s += 2) {
                            if (c) mbar_wait(bar + 8 * (B_EA + s), (c & 1) ^ 1);
                            if (s >= DA && c < 3) mbar_wait(fb - 8 * DA, 0);
                            bulk_ld(smb + OFF_A + s * 8192, src, (c == 3 && s == 7) ? 4096 : bytes, fb);
                            src += step; fb += 16;
                        }
                    }
                    if (!par) *(volatile unsigned*)&scr->epoch[blockIdx.x] = pre + 1;
                }
            } else if (warp < 12) {
                if (warp == 11) {
                    sync_publish(NB_R, 160, &scr->cnt[(C_H + 4 * ((lane >> 1) & 3) + 2 * rank + (lane & 1)) * 32], lane < 8);
                } else if (elect_one()) {
#pragma unroll 1
                    for (int c = 0; c < 5; c++) {
                        const uint4* s0 = c < 2 ? scr->h + (rr + 16 * c) * 4096 : scr->hh + (R2 * 176 + 8 * (c - 2)) * 64;
                        const uint4* s1 = s0 + (c < 2 ? 512 : c < 4 ? 28 * 64 : 6 * 64);
                        const uint32_t bytes = c < 4 ? 8192 : 6144, fb = bar + 8 * (c == 0 ? B_FA : c == 1 ? B_FL : B_G2 + 8 * (c - 2));
                        const unsigned* cp = &scr->cnt[(c < 2 ? C_H + rr + 16 * c : C_HH + rr * 3 + c - 2) * 32];
                        const unsigned target = (pre + 1) * (c < 2 ? 64 : 8);
                        if (c == 3) poll_ge(cp, target);
                        if (c == 0) mbar_wait(bar + 8 * B_OVL, 0);
                        else mbar_wait(bar + 8 * B_EA, (c & 1) ^ 1);
                        if (c != 3) poll_ge(cp, target);
                        mbar_arrive(bar + 8 * (B_FG + c));
                        asm volatile("fence.proxy.async.global;" ::: "memory");
                        bulk_ld(smb + OFF_A, s0, bytes, fb);
                        if (c) mbar_wait(bar + 8 * (B_EA + 1), (c & 1) ^ 1);
                        bulk_ld(smb + OFF_A + 8192, s1, bytes, fb + 8);
                    }
                }
            } else {
#pragma unroll 1
                for (int c = warp - 14; c < 3; c += 2) {
                    unsigned* cp = &scr->cnt[(C_HH + rr * 3 + c) * 32 + lane];
                    asm volatile("" : "+l"(cp));
                    sync_publish(NB_HH + c, 288, cp, lane == 0);
                    __syncwarp();
                }
            }
        }
    } else {
#pragma unroll
        for (int i = 0; i < 4; i++) ((uint4*)scr->sth)[((blockIdx.x - NCTA) * 4 + i) * 512 + tid] = make_uint4(0, 0, 0, 0);
        __syncthreads();
        if (warp == 0) {
            fence_gpu();
            if (lane < 16) red_add(&scr->cnt[(C_Z + lane) * 32]);
            if (elect_one()) {
                __nanosleep(PF_DELAY);
                const int o = (blockIdx.x - NCTA) * 11008;
#pragma unroll 1
                for (int i = 0; i < 32; i++) { l2_prefetch((const char*)w_gate + o + i * 44032, 11008); l2_prefetch((const char*)w_up + o + i * 44032, 11008); }
#pragma unroll 1
                for (int i = 0; i < 32; i++) l2_prefetch((const char*)w_down + o + i * 44032, 11008);
            }
        }
    }
}

namespace {
__device__ float block_sum(float v, float* red) {
    for (int o = 16; o; o >>= 1) v += __shfl_xor_sync(0xffffffffu, v, o);
    __syncthreads();
    if ((threadIdx.x & 31) == 0) red[threadIdx.x >> 5] = v;
    __syncthreads();
    float s = 0.f;
    for (int i = 0; i < D_ / 32; i++) s += red[i];
    return s;
}
__device__ float layer_norm(float v, float* red) {
    const float d = v - block_sum(v, red) * (1.f / D_);
    return d * rsqrtf(block_sum(d * d, red) * (1.f / D_) + LN_EPS);
}
}
__global__ void plain_kv_kernel(const __nv_bfloat16* k, const __nv_bfloat16* v, const __nv_bfloat16* sk, __nv_bfloat16* kv) {
    const int s = blockIdx.x, d = threadIdx.x;
    float a = 0.f;
    for (int j = 0; j < 4 && j <= s; j++) a += __bfloat162float(k[(s - j) * D_ + d]) * __bfloat162float(sk[d * 4 + j]);
    kv[s * D_ + d] = __float2bfloat16(a * __bfloat162float(v[s * D_ + d]));
}
__global__ void plain_h_kernel(const __nv_bfloat16* x, const __nv_bfloat16* kv, const __nv_bfloat16* ssm_k, const __nv_bfloat16* ssm_D, __nv_bfloat16* h) {
    __shared__ float red[D_ / 32];
    const int s = blockIdx.x, d = threadIdx.x;
    float y = __bfloat162float(kv[s * D_ + d]) * __bfloat162float(ssm_D[d]);
    for (int j = 0; j <= s; j++) y += __bfloat162float(kv[(s - j) * D_ + d]) * __bfloat162float(ssm_k[d * S_ + j]);
    const float xv = __bfloat162float(x[s * D_ + d]);
    h[s * D_ + d] = __float2bfloat16(xv + layer_norm(xv, red) * y);
}
__global__ void plain_ffn_kernel(const __nv_bfloat16* h, const __nv_bfloat16* wg, const __nv_bfloat16* wu, const __nv_bfloat16* wd, __nv_bfloat16* out) {
    __shared__ float red[D_ / 32], a[D_], hh[F_];
    const int s = blockIdx.x, d = threadIdx.x;
    const float hv = __bfloat162float(h[s * D_ + d]);
    a[d] = layer_norm(hv, red);
    __syncthreads();
    for (int f = d; f < F_; f += D_) {
        float g = 0.f, u = 0.f;
        for (int k = 0; k < D_; k++) { g += a[k] * __bfloat162float(wg[k * F_ + f]); u += a[k] * __bfloat162float(wu[k * F_ + f]); }
        hh[f] = 0.5f * g * (1.f + tanhf(0.7978845608028654f * (g + 0.044715f * g * g * g))) * u;
    }
    __syncthreads();
    float o = hv;
    for (int f = 0; f < F_; f++) o += hh[f] * __bfloat162float(wd[f * D_ + d]);
    out[s * D_ + d] = __float2bfloat16(o);
}

namespace {

typedef CUresult (*EncodeFn)(CUtensorMap*, CUtensorMapDataType, cuuint32_t, void*, const cuuint64_t*, const cuuint64_t*, const cuuint32_t*,
                             const cuuint32_t*, CUtensorMapInterleave, CUtensorMapSwizzle, CUtensorMapL2promotion, CUtensorMapFloatOOBfill);

void encode(EncodeFn fn, CUtensorMap* m, const void* base, int rank, const cuuint64_t* dims, const cuuint64_t* strides, const cuuint32_t* box,
            CUtensorMapSwizzle sw) {
    const cuuint32_t es[3] = {1, 1, 1};
    fn(m, CU_TENSOR_MAP_DATA_TYPE_BFLOAT16, rank, const_cast<void*>(base), dims, strides, box, es, CU_TENSOR_MAP_INTERLEAVE_NONE, sw,
       CU_TENSOR_MAP_L2_PROMOTION_L2_128B, CU_TENSOR_MAP_FLOAT_OOB_FILL_NONE);
}

}

extern "C" void kernel_launch(void* const* d_in, const int* in_sizes, int n_in, void* d_out, int out_size) {
    (void)in_sizes; (void)n_in; (void)out_size;
    const __nv_bfloat16* x = (const __nv_bfloat16*)d_in[0];
    const __nv_bfloat16* wgate = (const __nv_bfloat16*)d_in[7];
    const __nv_bfloat16* wup = (const __nv_bfloat16*)d_in[8];
    const __nv_bfloat16* wdown = (const __nv_bfloat16*)d_in[9];

    void* scr = nullptr;
    cudaGetSymbolAddress(&scr, g_scr);
    void* fnp = nullptr;
    cudaDriverEntryPointQueryResult qr;
    cudaGetDriverEntryPoint("cuTensorMapEncodeTiled", &fnp, cudaEnableDefault, &qr);
    EncodeFn fn = (EncodeFn)fnp;
    int clusters = 0;
    if (cudaFuncSetAttribute(h3_geglu_kernel, cudaFuncAttributeMaxDynamicSharedMemorySize, SMEM_BYTES) == cudaSuccess) {
        cudaLaunchConfig_t cfg = {};
        cudaLaunchAttribute at;
        at.id = cudaLaunchAttributeClusterDimension;
        at.val.clusterDim.x = 2; at.val.clusterDim.y = 1; at.val.clusterDim.z = 1;
        cfg.gridDim = dim3(NGRID); cfg.blockDim = dim3(NTHR); cfg.dynamicSmemBytes = SMEM_BYTES; cfg.attrs = &at; cfg.numAttrs = 1;
        if (cudaOccupancyMaxActiveClusters(&clusters, h3_geglu_kernel, &cfg) != cudaSuccess) clusters = 0;
    }
    if (!fn || clusters < NGRID / 2) {
        (void)cudaGetLastError();
        __nv_bfloat16 *o = (__nv_bfloat16*)d_out, *h = (__nv_bfloat16*)((Scratch*)scr)->h;
        plain_kv_kernel<<<S_, D_>>>((const __nv_bfloat16*)d_in[1], (const __nv_bfloat16*)d_in[2], (const __nv_bfloat16*)d_in[3], o);
        plain_h_kernel<<<S_, D_>>>(x, o, (const __nv_bfloat16*)d_in[4], (const __nv_bfloat16*)d_in[5], h);
        plain_ffn_kernel<<<S_, D_>>>(h, wgate, wup, wdown, o);
        return;
    }
    Params p;
    {
        const cuuint64_t dims[3] = {D_, S_ / 4, 4}, str[2] = {4 * D_ * 2, D_ * 2};
        const cuuint32_t box[3] = {8, 33, 4};
        encode(fn, &p.k, d_in[1], 3, dims, str, box, CU_TENSOR_MAP_SWIZZLE_NONE);
        encode(fn, &p.v, d_in[2], 3, dims, str, box, CU_TENSOR_MAP_SWIZZLE_NONE);
    }
    {
        const cuuint32_t bx[3] = {8, 128, 4};
        const cuuint64_t dx[3] = {D_, 256, 8}, sx[2] = {D_ * 2, 256 * D_ * 2};
        encode(fn, &p.x, x, 3, dx, sx, bx, CU_TENSOR_MAP_SWIZZLE_NONE);
    }
    {
        const cuuint64_t dims[2] = {F_, D_}, str[1] = {F_ * 2};
        const cuuint32_t box[2] = {64, 64};
        encode(fn, &p.wg, wgate, 2, dims, str, box, CU_TENSOR_MAP_SWIZZLE_128B);
        encode(fn, &p.wu, wup, 2, dims, str, box, CU_TENSOR_MAP_SWIZZLE_128B);
    }
    {
        const cuuint64_t dims[2] = {D_, F_}, str[1] = {D_ * 2};
        const cuuint32_t b64[2] = {64, 64}, b48[2] = {64, 48};
        encode(fn, &p.wd, wdown, 2, dims, str, b64, CU_TENSOR_MAP_SWIZZLE_128B);
        encode(fn, &p.wd48, wdown, 2, dims, str, b48, CU_TENSOR_MAP_SWIZZLE_128B);
    }
    h3_geglu_kernel<<<NGRID, NTHR, SMEM_BYTES>>>((const __nv_bfloat16*)d_in[4], (Scratch*)scr, x, (const __nv_bfloat16*)d_in[3],
                                                 (const __nv_bfloat16*)d_in[5], (__nv_bfloat16*)d_out, wgate, wup, wdown, p);
}
```
